```python
import torch

def _softmax(x, axis=-1):
    return torch.softmax(x, dim=axis)
def _gelu(x):
    return torch.nn.functional.gelu(x, approximate="tanh")
def _silu(x):
    return torch.nn.functional.silu(x)
def _sigmoid(x):
    return torch.sigmoid(x)
def _layernorm(x, axis=-1, eps=1e-5):
    m = x.mean(dim=axis, keepdim=True)
    v = x.var(dim=axis, keepdim=True, unbiased=False)
    return (x - m) / torch.sqrt(v + eps)
def _scatter_add(tgt, idx, src, axis=0):
    return tgt.clone().index_add_(axis, idx, src)
def _segment_sum(src, seg, n):
    out = torch.zeros((n,) + src.shape[1:], dtype=src.dtype)
    return out.index_add_(0, seg, src)
def _pad(x, pw):
    flat = tuple(v for pair in reversed(pw) for v in pair)
    return torch.nn.functional.pad(x, flat)

kernel_name = 'parallel_sum__gqa_block_cached__mixer_channel_mlp__decode'

def setup_inputs():

    _w = (lambda a: (lambda t: t.to(torch.bfloat16) if t.is_floating_point() else t)(torch.as_tensor(a)))
    def _A_setup():
        B, Sq, D = 1, 1, 640
        Hq, Hkv, Sk, Dh = 32, 32, 16384, 128
        assert Hq % Hkv == 0, (Hq, Hkv)
        return {
            "x": _w((lambda *s: torch.randn(*s, dtype=torch.bfloat16) * 0.05)(B, Sq, D)),
            "k_cache": _w((lambda *s: torch.randn(*s, dtype=torch.bfloat16) * 3.2)(B, Hkv, Sk, Dh)),
            "v_cache": _w((lambda *s: torch.randn(*s, dtype=torch.bfloat16) * 0.4)(B, Hkv, Sk, Dh)),
            "wq": _w((lambda *s: torch.randn(*s, dtype=torch.bfloat16) * 3.2)(D, Hq * Dh) * (D ** -0.5)),
            "wo": _w((lambda *s: torch.randn(*s, dtype=torch.bfloat16) * 0.4)(Hq * Dh, D) * ((Hq * Dh) ** -0.5)),
        }
    _A_in = _A_setup()

    def _B_setup():
        B, S, D, F = 1, 1, 640, 1728
        return {
            "x": _w((lambda *s: torch.randn(*s, dtype=torch.bfloat16) * 0.05)(B, S, D)),
            "w1": _w((lambda *s: torch.randn(*s, dtype=torch.bfloat16) * 3.2)(D, F) * (D ** -0.5)),
            "b1": _w((lambda *s: torch.randn(*s, dtype=torch.bfloat16) * 0.8)(F)),
            "w2": _w((lambda *s: torch.randn(*s, dtype=torch.bfloat16) * 0.1)(F, D) * (F ** -0.5)),
            "b2": _w((lambda *s: torch.randn(*s, dtype=torch.bfloat16) * 0.1)(D)),
        }
    _B_in = _B_setup()

    return {
        "A_x": _A_in["x"],
        "A_k_cache": _A_in["k_cache"],
        "A_v_cache": _A_in["v_cache"],
        "A_wq": _A_in["wq"],
        "A_wo": _A_in["wo"],
        "B_x": _B_in["x"],
        "B_w1": _B_in["w1"],
        "B_b1": _B_in["b1"],
        "B_w2": _B_in["w2"],
        "B_b2": _B_in["b2"],
    }

def reference(A_x, A_k_cache, A_v_cache, A_wq, A_wo, B_x, B_w1, B_b1, B_w2, B_b2):
    def _A_ref(x, k_cache, v_cache, wq, wo):
        B, Sq, D = x.shape
        Hq, Dh = 32, 128
        Hkv = k_cache.shape[1]
        rep = Hq // Hkv
        q = (lambda x, *d: x.permute(*d))((x @ wq).reshape(B, Sq, Hq, Dh), 0, 2, 1, 3)
        k = (lambda x, n, axis: torch.repeat_interleave(x, n, dim=axis))(k_cache, rep, axis=1)
        v = (lambda x, n, axis: torch.repeat_interleave(x, n, dim=axis))(v_cache, rep, axis=1)
        scores = torch.einsum("bhqd,bhkd->bhqk", q, k) * (Dh ** -0.5)
        p = _softmax(scores, axis=-1)
        o = torch.einsum("bhqk,bhkd->bhqd", p, v)
        return (lambda x, *d: x.permute(*d))(o, 0, 2, 1, 3).reshape(B, Sq, Hq * Dh) @ wo

    def _B_ref(x, w1, b1, w2, b2):
        y = _layernorm(x, axis=-1)
        h = _gelu(torch.einsum("bsd,df->bsf", y, w1) + b1)
        return torch.einsum("bsf,fd->bsd", h, w2) + b2

    x = A_x
    xn = _layernorm(x, axis=-1)
    return x + _A_ref(xn, A_k_cache, A_v_cache, A_wq, A_wo) + _B_ref(xn, B_w1, B_b1, B_w2, B_b2)
```

```cpp
#include <cuda_runtime.h>
#include <cuda_bf16.h>
#include <stdint.h>

namespace {

constexpr int D_MODEL = 640;
constexpr int NHEAD = 32;
constexpr int SK = 16384;
constexpr int DH = 128;
constexpr int FF = 1728;
constexpr int NSPLIT = 4;
constexpr int NCTA = NHEAD * NSPLIT;
constexpr int KEYS_PER_CTA = SK / NSPLIT;
constexpr int TILE = 64;
constexpr int TILE_BYTES = TILE * DH * 2;
constexpr int NT = KEYS_PER_CTA / TILE;
constexpr int STAGES = 10;
constexpr int WO_ROWS = DH / NSPLIT;
constexpr int WO_BYTES = WO_ROWS * D_MODEL * 2;
constexpr int MLP_COLS = 16;
constexpr int MLP_CTAS = FF / MLP_COLS;
constexpr int NTHREADS = 320;

constexpr int OFF_RING = 0;
constexpr int OFF_WO = OFF_RING + STAGES * TILE_BYTES;
constexpr int OFF_SC = OFF_WO + WO_BYTES;
constexpr int OFF_XN = OFF_SC + KEYS_PER_CTA * 4;
constexpr int OFF_Q = OFF_XN + D_MODEL * 4;
constexpr int OFF_RED = OFF_Q + DH * 4;
constexpr int OFF_MISC = OFF_RED + 8 * DH * 4;
constexpr int OFF_BAR = OFF_MISC + 256;
constexpr int SMEM_BYTES = OFF_BAR + (2 * STAGES + 1) * 8;

__device__ unsigned long long g_ml[NCTA];
__device__ float g_opart[NCTA * DH];
__device__ unsigned int g_oflag[NCTA];
__device__ float g_accA[D_MODEL];
__device__ float g_accB[D_MODEL];
__device__ unsigned int g_done;

__device__ __forceinline__ uint32_t s2u(const void* p) { return (uint32_t)__cvta_generic_to_shared(p); }
__device__ __forceinline__ void mbar_init(uint32_t a, uint32_t c) {
    asm volatile("mbarrier.init.shared::cta.b64 [%0], %1;" ::"r"(a), "r"(c));
}
__device__ __forceinline__ void mbar_expect(uint32_t a, uint32_t b) {
    asm volatile("mbarrier.arrive.expect_tx.shared::cta.b64 _, [%0], %1;" ::"r"(a), "r"(b) : "memory");
}
__device__ __forceinline__ void mbar_arrive(uint32_t a) {
    asm volatile("mbarrier.arrive.shared::cta.b64 _, [%0];" ::"r"(a) : "memory");
}
__device__ __forceinline__ void mbar_wait(uint32_t a, uint32_t ph) {
    uint32_t ok;
    int it = 0;
    do {
        asm volatile(
            "{\n.reg .pred p;\nmbarrier.try_wait.parity.shared::cta.b64 p, [%1], %2;\nselp.u32 %0,1,0,p;\n}"
            : "=r"(ok)
            : "r"(a), "r"(ph)
            : "memory");
        if (++it > (1 << 22)) __trap();
    } while (!ok);
}
__device__ __forceinline__ void bulk_g2s(uint32_t dst, const void* src, uint32_t bytes, uint32_t bar) {
    asm volatile("cp.async.bulk.shared::cluster.global.mbarrier::complete_tx::bytes [%0], [%1], %2, [%3];" ::"r"(dst),
                 "l"(src), "r"(bytes), "r"(bar)
                 : "memory");
}
__device__ __forceinline__ void cbar() { asm volatile("bar.sync 1, 256;" ::: "memory"); }

__device__ __forceinline__ float bfr(float x) { return __bfloat162float(__float2bfloat16_rn(x)); }
__device__ __forceinline__ float bflo(uint32_t u) { return __uint_as_float(u << 16); }
__device__ __forceinline__ float bfhi(uint32_t u) { return __uint_as_float(u & 0xffff0000u); }

__device__ __forceinline__ uint4 ldg_nc16(const void* p) {
    uint4 v;
    asm volatile("ld.global.nc.L1::no_allocate.v4.u32 {%0,%1,%2,%3}, [%4];"
                 : "=r"(v.x), "=r"(v.y), "=r"(v.z), "=r"(v.w)
                 : "l"(p));
    return v;
}
__device__ __forceinline__ uint2 ldg_nc8(const void* p) {
    uint2 v;
    asm volatile("ld.global.nc.L1::no_allocate.v2.u32 {%0,%1}, [%2];" : "=r"(v.x), "=r"(v.y) : "l"(p));
    return v;
}
__device__ __forceinline__ float warp_sum(float v) {
#pragma unroll
    for (int o = 16; o > 0; o >>= 1) v += __shfl_xor_sync(0xffffffffu, v, o);
    return v;
}
__device__ __forceinline__ float warp_max(float v) {
#pragma unroll
    for (int o = 16; o > 0; o >>= 1) v = fmaxf(v, __shfl_xor_sync(0xffffffffu, v, o));
    return v;
}

__device__ __forceinline__ void fma8(float* acc, float s, const uint4& v) {
    acc[0] = fmaf(s, bflo(v.x), acc[0]);
    acc[1] = fmaf(s, bfhi(v.x), acc[1]);
    acc[2] = fmaf(s, bflo(v.y), acc[2]);
    acc[3] = fmaf(s, bfhi(v.y), acc[3]);
    acc[4] = fmaf(s, bflo(v.z), acc[4]);
    acc[5] = fmaf(s, bfhi(v.z), acc[5]);
    acc[6] = fmaf(s, bflo(v.w), acc[6]);
    acc[7] = fmaf(s, bfhi(v.w), acc[7]);
}
__device__ __forceinline__ float dot8(const float* q, const uint4& v) {
    float a = q[0] * bflo(v.x);
    float b = q[1] * bfhi(v.x);
    a = fmaf(q[2], bflo(v.y), a);
    b = fmaf(q[3], bfhi(v.y), b);
    a = fmaf(q[4], bflo(v.z), a);
    b = fmaf(q[5], bfhi(v.z), b);
    a = fmaf(q[6], bflo(v.w), a);
    b = fmaf(q[7], bfhi(v.w), b);
    return a + b;
}

__device__ __forceinline__ void warp_layernorm(float* v) {
    float s = 0.f;
#pragma unroll
    for (int i = 0; i < 20; i++) s += v[i];
    s = warp_sum(s);
    const float mean = s * (1.0f / D_MODEL);
    float ss = 0.f;
#pragma unroll
    for (int i = 0; i < 20; i++) {
        float d = v[i] - mean;
        ss = fmaf(d, d, ss);
    }
    ss = warp_sum(ss);
    const float m_bf = bfr(mean);
    const float v_bf = bfr(ss * (1.0f / D_MODEL));
    const float den = bfr(sqrtf(bfr(v_bf + 1e-5f)));
#pragma unroll
    for (int i = 0; i < 20; i++) v[i] = bfr(__fdiv_rn(bfr(v[i] - m_bf), den));
}

__global__ void __launch_bounds__(NTHREADS, 1)
fused_decode_kernel(const __nv_bfloat16* __restrict__ x, const __nv_bfloat16* __restrict__ kc,
                    const __nv_bfloat16* __restrict__ vc, const __nv_bfloat16* __restrict__ wq,
                    const __nv_bfloat16* __restrict__ wo, const __nv_bfloat16* __restrict__ w1,
                    const __nv_bfloat16* __restrict__ b1, const __nv_bfloat16* __restrict__ w2,
                    const __nv_bfloat16* __restrict__ b2, __nv_bfloat16* __restrict__ out) {
    extern __shared__ __align__(1024) unsigned char smem[];
    const int tid = threadIdx.x, warp = tid >> 5, lane = tid & 31;
    const int cta = blockIdx.x, head = cta >> 2, split = cta & 3;

    float* sc = reinterpret_cast<float*>(smem + OFF_SC);
    float* xn_s = reinterpret_cast<float*>(smem + OFF_XN);
    float* q_s = reinterpret_cast<float*>(smem + OFF_Q);
    float* red = reinterpret_cast<float*>(smem + OFF_RED);
    float* misc = reinterpret_cast<float*>(smem + OFF_MISC);
    const uint32_t bar_full = s2u(smem + OFF_BAR);
    const uint32_t bar_empty = bar_full + STAGES * 8;
    const uint32_t bar_wo = bar_full + 2 * STAGES * 8;

    if (tid == 0) {
        for (int i = 0; i < STAGES; i++) {
            mbar_init(bar_full + i * 8, 1);
            mbar_init(bar_empty + i * 8, 8);
        }
        mbar_init(bar_wo, 1);
        asm volatile("fence.mbarrier_init.release.cluster;" ::: "memory");
    }
    __syncthreads();

    if (warp == 8) {
        if (lane == 0) {
            const unsigned char* kbase =
                reinterpret_cast<const unsigned char*>(kc) + ((size_t)head * SK + (size_t)split * KEYS_PER_CTA) * (DH * 2);
            const unsigned char* vbase =
                reinterpret_cast<const unsigned char*>(vc) + ((size_t)head * SK + (size_t)split * KEYS_PER_CTA) * (DH * 2);
            const uint32_t ring = s2u(smem + OFF_RING);
            int s = 0;
            uint32_t ph = 1;
            for (int t = 0; t < 2 * NT; t++) {
                mbar_wait(bar_empty + s * 8, ph);
                mbar_expect(bar_full + s * 8, TILE_BYTES);
                const unsigned char* src = (t < NT) ? (kbase + (size_t)t * TILE_BYTES) : (vbase + (size_t)(t - NT) * TILE_BYTES);
                bulk_g2s(ring + s * TILE_BYTES, src, TILE_BYTES, bar_full + s * 8);
                if (t == STAGES - 1) {
                    mbar_expect(bar_wo, WO_BYTES);
                    bulk_g2s(s2u(smem + OFF_WO),
                             reinterpret_cast<const unsigned char*>(wo) + (size_t)(head * DH + split * WO_ROWS) * (D_MODEL * 2),
                             WO_BYTES, bar_wo);
                }
                if (++s == STAGES) { s = 0; ph ^= 1; }
            }
        }
    } else if (warp == 9) {
        if (cta < MLP_CTAS) {
            const int f0 = cta * MLP_COLS;
            float v[20];
#pragma unroll
            for (int i = 0; i < 20; i++) v[i] = __bfloat162float(x[lane + 32 * i]);
            warp_layernorm(v);
            warp_layernorm(v);
            float acc[8];
#pragma unroll
            for (int i = 0; i < 8; i++) acc[i] = 0.f;
            const unsigned char* w1p = reinterpret_cast<const unsigned char*>(w1) + (size_t)f0 * 2 + (lane & 1) * 16;
#pragma unroll
            for (int b = 0; b < 4; b++) {
                uint4 wv[10];
#pragma unroll
                for (int i = 0; i < 10; i++) {
                    const int row = (b * 10 + i) * 16 + (lane >> 1);
                    wv[i] = ldg_nc16(w1p + (size_t)row * (FF * 2));
                }
#pragma unroll
                for (int i = 0; i < 10; i++) {
                    const int row = (b * 10 + i) * 16 + (lane >> 1);
                    const int reg = (b * 10 + i) >> 1;
                    const float yv = __shfl_sync(0xffffffffu, v[reg], row & 31);
                    fma8(acc, yv, wv[i]);
                }
            }
#pragma unroll
            for (int i = 0; i < 8; i++) {
#pragma unroll
                for (int o = 2; o <= 16; o <<= 1) acc[i] += __shfl_xor_sync(0xffffffffu, acc[i], o);
            }
            float hval[8];
#pragma unroll
            for (int i = 0; i < 8; i++) {
                const int f = f0 + (lane & 1) * 8 + i;
                const float pre = bfr(bfr(acc[i]) + __bfloat162float(b1[f]));
                const float inner = 0.7978845608028654f * (pre + 0.044715f * pre * pre * pre);
                hval[i] = bfr(0.5f * pre * (1.0f + tanhf(inner)));
            }
            float o[20];
#pragma unroll
            for (int i = 0; i < 20; i++) o[i] = 0.f;
            const unsigned char* w2p = reinterpret_cast<const unsigned char*>(w2) + (size_t)f0 * (D_MODEL * 2) + lane * 8;
#pragma unroll
            for (int rb = 0; rb < 2; rb++) {
                uint2 wv[8][5];
#pragma unroll
                for (int r = 0; r < 8; r++)
#pragma unroll
                    for (int i = 0; i < 5; i++) wv[r][i] = ldg_nc8(w2p + (size_t)(rb * 8 + r) * (D_MODEL * 2) + i * 256);
#pragma unroll
                for (int r = 0; r < 8; r++) {
                    const float hv = __shfl_sync(0xffffffffu, hval[r], rb);
#pragma unroll
                    for (int i = 0; i < 5; i++) {
                        o[i * 4 + 0] = fmaf(hv, bflo(wv[r][i].x), o[i * 4 + 0]);
                        o[i * 4 + 1] = fmaf(hv, bfhi(wv[r][i].x), o[i * 4 + 1]);
                        o[i * 4 + 2] = fmaf(hv, bflo(wv[r][i].y), o[i * 4 + 2]);
                        o[i * 4 + 3] = fmaf(hv, bfhi(wv[r][i].y), o[i * 4 + 3]);
                    }
                }
            }
#pragma unroll
            for (int i = 0; i < 5; i++)
#pragma unroll
                for (int j = 0; j < 4; j++) atomicAdd(&g_accB[(lane + 32 * i) * 4 + j], o[i * 4 + j]);
            __threadfence();
        }
    } else {
        const unsigned char* wqp =
            reinterpret_cast<const unsigned char*>(wq) + (size_t)head * (DH * 2) + (tid & 15) * 16 + (size_t)(tid >> 4) * (NHEAD * DH * 2);
        uint4 wv[20];
#pragma unroll
        for (int i = 0; i < 20; i++) wv[i] = ldg_nc16(wqp + (size_t)i * 16 * (NHEAD * DH * 2));

        if (warp == 0) {
            float v[20];
#pragma unroll
            for (int i = 0; i < 20; i++) v[i] = __bfloat162float(x[lane + 32 * i]);
            warp_layernorm(v);
#pragma unroll
            for (int i = 0; i < 20; i++) xn_s[lane + 32 * i] = v[i];
        }
        cbar();
        float qa[8];
#pragma unroll
        for (int i = 0; i < 8; i++) qa[i] = 0.f;
#pragma unroll
        for (int i = 0; i < 20; i++) fma8(qa, xn_s[i * 16 + (tid >> 4)], wv[i]);
#pragma unroll
        for (int i = 0; i < 20; i++) wv[i] = ldg_nc16(wqp + (size_t)(i + 20) * 16 * (NHEAD * DH * 2));
#pragma unroll
        for (int i = 0; i < 20; i++) fma8(qa, xn_s[(i + 20) * 16 + (tid >> 4)], wv[i]);
#pragma unroll
        for (int i = 0; i < 8; i++) qa[i] += __shfl_xor_sync(0xffffffffu, qa[i], 16);
        if (lane < 16) {
#pragma unroll
            for (int i = 0; i < 8; i++) red[warp * DH + lane * 8 + i] = qa[i];
        }
        cbar();
        if (tid < DH) {
            float s = 0.f;
#pragma unroll
            for (int w = 0; w < 8; w++) s += red[w * DH + tid];
            q_s[tid] = bfr(s);
        }
        cbar();
        float q[8];
#pragma unroll
        for (int i = 0; i < 8; i++) q[i] = q_s[(lane & 15) * 8 + i];

        const float scale = 0.08838834764831845f;
        const unsigned char* ring = smem + OFF_RING;
        int s = 0;
        uint32_t ph = 0;
        float mloc = -INFINITY;
        const int lane_off = (warp * 8 + (lane >> 4)) * (DH * 2) + (lane & 15) * 16;
        for (int t = 0; t < NT; t++) {
            mbar_wait(bar_full + s * 8, ph);
            const unsigned char* tp = ring + s * TILE_BYTES + lane_off;
            uint4 kv[4];
#pragma unroll
            for (int j = 0; j < 4; j++) kv[j] = *reinterpret_cast<const uint4*>(tp + j * 2 * (DH * 2));
            float a0 = dot8(q, kv[0]), a1 = dot8(q, kv[1]), a2 = dot8(q, kv[2]), a3 = dot8(q, kv[3]);
            __syncwarp();
            if (lane == 0) mbar_arrive(bar_empty + s * 8);
            const bool b3 = lane & 8, b2 = lane & 4;
            float s0 = b3 ? a0 : a2, s1 = b3 ? a1 : a3;
            float k0 = b3 ? a2 : a0, k1 = b3 ? a3 : a1;
            k0 += __shfl_xor_sync(0xffffffffu, s0, 8);
            k1 += __shfl_xor_sync(0xffffffffu, s1, 8);
            float sn = b2 ? k0 : k1, kp = b2 ? k1 : k0;
            kp += __shfl_xor_sync(0xffffffffu, sn, 4);
            kp += __shfl_xor_sync(0xffffffffu, kp, 2);
            kp += __shfl_xor_sync(0xffffffffu, kp, 1);
            const float sv = bfr(bfr(kp) * scale);
            mloc = fmaxf(mloc, sv);
            const int j = (b3 ? 2 : 0) + (b2 ? 1 : 0);
            if ((lane & 3) == 0) sc[t * TILE + warp * 8 + 2 * j + (lane >> 4)] = sv;
            if (++s == STAGES) { s = 0; ph ^= 1; }
        }

        mloc = warp_max(mloc);
        if (lane == 0) misc[warp] = mloc;
        cbar();
        float mcta = misc[0];
#pragma unroll
        for (int w = 1; w < 8; w++) mcta = fmaxf(mcta, misc[w]);
        float lsum = 0.f;
#pragma unroll
        for (int i = 0; i < KEYS_PER_CTA / 256; i++) lsum += expf(sc[tid + 256 * i] - mcta);
        lsum = warp_sum(lsum);
        if (lane == 0) misc[8 + warp] = lsum;
        cbar();
        if (warp == 0) {
            float l = 0.f;
#pragma unroll
            for (int w = 0; w < 8; w++) l += misc[8 + w];
            if (lane == 0) {
                unsigned long long pk = ((unsigned long long)__float_as_uint(l) << 32) | __float_as_uint(mcta);
                asm volatile("st.relaxed.gpu.global.u64 [%0], %1;" ::"l"(&g_ml[cta]), "l"(pk) : "memory");
            }
            float mj = -INFINITY, lj = 0.f;
            if (lane < NSPLIT) {
                unsigned long long pk;
                int it = 0;
                do {
                    asm volatile("ld.relaxed.gpu.global.u64 %0, [%1];" : "=l"(pk) : "l"(&g_ml[head * NSPLIT + lane]) : "memory");
                    if (++it > (1 << 24)) __trap();
                } while ((pk >> 32) == 0ull);
                mj = __uint_as_float((uint32_t)pk);
                lj = __uint_as_float((uint32_t)(pk >> 32));
            }
            float mg = fmaxf(mj, __shfl_xor_sync(0xffffffffu, mj, 1));
            mg = fmaxf(mg, __shfl_xor_sync(0xffffffffu, mg, 2));
            float lg = (lane < NSPLIT) ? lj * expf(mj - mg) : 0.f;
            lg += __shfl_xor_sync(0xffffffffu, lg, 1);
            lg += __shfl_xor_sync(0xffffffffu, lg, 2);
            if (lane == 0) { misc[16] = mg; misc[17] = lg; }
        }
        cbar();
        {
            const float mg = misc[16], lg = misc[17];
#pragma unroll
            for (int i = 0; i < KEYS_PER_CTA / 256; i++) {
                const int k = tid + 256 * i;
                sc[k] = bfr(__fdiv_rn(expf(sc[k] - mg), lg));
            }
        }
        cbar();

        float oa[8];
#pragma unroll
        for (int i = 0; i < 8; i++) oa[i] = 0.f;
        for (int t = 0; t < NT; t++) {
            mbar_wait(bar_full + s * 8, ph);
            const unsigned char* tp = ring + s * TILE_BYTES + lane_off;
            uint4 vv[4];
            float p[4];
#pragma unroll
            for (int j = 0; j < 4; j++) {
                vv[j] = *reinterpret_cast<const uint4*>(tp + j * 2 * (DH * 2));
                p[j] = sc[t * TILE + warp * 8 + 2 * j + (lane >> 4)];
            }
#pragma unroll
            for (int j = 0; j < 4; j++) fma8(oa, p[j], vv[j]);
            __syncwarp();
            if (lane == 0) mbar_arrive(bar_empty + s * 8);
            if (++s == STAGES) { s = 0; ph ^= 1; }
        }
#pragma unroll
        for (int i = 0; i < 8; i++) oa[i] += __shfl_xor_sync(0xffffffffu, oa[i], 16);
        if (lane < 16) {
#pragma unroll
            for (int i = 0; i < 8; i++) red[warp * DH + lane * 8 + i] = oa[i];
        }
        cbar();
        if (tid < DH) {
            float v = 0.f;
#pragma unroll
            for (int w = 0; w < 8; w++) v += red[w * DH + tid];
            __stcg(&g_opart[cta * DH + tid], v);
            __threadfence();
        }
        cbar();
        if (tid == 0) {
            asm volatile("st.release.gpu.global.u32 [%0], %1;" ::"l"(&g_oflag[cta]), "r"(1u) : "memory");
        }
        if (warp == 0) {
            if (lane < NSPLIT) {
                unsigned int f;
                int it = 0;
                do {
                    asm volatile("ld.acquire.gpu.global.u32 %0, [%1];" : "=r"(f) : "l"(&g_oflag[head * NSPLIT + lane]) : "memory");
                    if (++it > (1 << 24)) __trap();
                } while (f == 0);
            }
            __syncwarp();
            __threadfence();
            float v = 0.f;
#pragma unroll
            for (int j = 0; j < NSPLIT; j++) v += __ldcg(&g_opart[(head * NSPLIT + j) * DH + split * WO_ROWS + lane]);
            misc[32 + lane] = bfr(v);
        }
        cbar();
        mbar_wait(bar_wo, 0);
        if (tid < 160) {
            float a0 = 0.f, a1 = 0.f, a2 = 0.f, a3 = 0.f;
            const unsigned char* wp = smem + OFF_WO + tid * 8;
#pragma unroll 8
            for (int r = 0; r < WO_ROWS; r++) {
                const uint2 w = *reinterpret_cast<const uint2*>(wp + r * (D_MODEL * 2));
                const float ov = misc[32 + r];
                a0 = fmaf(ov, bflo(w.x), a0);
                a1 = fmaf(ov, bfhi(w.x), a1);
                a2 = fmaf(ov, bflo(w.y), a2);
                a3 = fmaf(ov, bfhi(w.y), a3);
            }
            atomicAdd(&g_accA[tid * 4 + 0], a0);
            atomicAdd(&g_accA[tid * 4 + 1], a1);
            atomicAdd(&g_accA[tid * 4 + 2], a2);
            atomicAdd(&g_accA[tid * 4 + 3], a3);
            __threadfence();
        }
    }

    __syncthreads();
    __shared__ unsigned int s_last;
    if (tid == 0) {
        __threadfence();
        s_last = (atomicAdd(&g_done, 1u) == (unsigned)(NCTA - 1)) ? 1u : 0u;
        __threadfence();
    }
    __syncthreads();
    if (s_last) {
        for (int c = tid; c < D_MODEL; c += NTHREADS) {
            const float a = bfr(__ldcg(&g_accA[c]));
            const float b = bfr(bfr(__ldcg(&g_accB[c])) + __bfloat162float(b2[c]));
            const float r = bfr(bfr(__bfloat162float(x[c]) + a) + b);
            out[c] = __float2bfloat16_rn(r);
            __stcg(&g_accA[c], 0.f);
            __stcg(&g_accB[c], 0.f);
        }
        if (tid < NCTA) {
            g_ml[tid] = 0ull;
            g_oflag[tid] = 0u;
        }
        if (tid == 0) g_done = 0u;
    }
}

}

extern "C" void kernel_launch(void* const* d_in, const int* in_sizes, int n_in, void* d_out, int out_size) {
    const __nv_bfloat16* x = (const __nv_bfloat16*)d_in[0];
    const __nv_bfloat16* kc = (const __nv_bfloat16*)d_in[1];
    const __nv_bfloat16* vc = (const __nv_bfloat16*)d_in[2];
    const __nv_bfloat16* wq = (const __nv_bfloat16*)d_in[3];
    const __nv_bfloat16* wo = (const __nv_bfloat16*)d_in[4];
    const __nv_bfloat16* w1 = (const __nv_bfloat16*)d_in[6];
    const __nv_bfloat16* b1 = (const __nv_bfloat16*)d_in[7];
    const __nv_bfloat16* w2 = (const __nv_bfloat16*)d_in[8];
    const __nv_bfloat16* b2 = (const __nv_bfloat16*)d_in[9];
    static bool attr_set = false;
    if (!attr_set) {
        cudaFuncSetAttribute(fused_decode_kernel, cudaFuncAttributeMaxDynamicSharedMemorySize, SMEM_BYTES);
        attr_set = true;
    }
    fused_decode_kernel<<<NCTA, NTHREADS, SMEM_BYTES>>>(x, kc, vc, wq, wo, w1, b1, w2, b2, (__nv_bfloat16*)d_out);
}
```

```cpp
#include <cuda_runtime.h>
#include <cuda_bf16.h>
#include <stdint.h>

namespace {

constexpr int D_MODEL = 640;
constexpr int NHEAD = 32;
constexpr int SK = 16384;
constexpr int DH = 128;
constexpr int FF = 1728;
constexpr int NSPLIT = 4;
constexpr int NCTA = NHEAD * NSPLIT;
constexpr int KEYS_PER_CTA = SK / NSPLIT;
constexpr int TILE = 64;
constexpr int TILE_BYTES = TILE * DH * 2;
constexpr int NT = KEYS_PER_CTA / TILE;
constexpr int STAGES = 10;
#define INFLIGHT_N 4
constexpr int INFLIGHT = INFLIGHT_N;
#define PACE_OFF 2
#define PACE_HI 2
#define INFLIGHT_LO 2
#define INFLIGHT_HI 8
constexpr int WO_ROWS = DH / NSPLIT;
constexpr int WO_BYTES = WO_ROWS * D_MODEL * 2;
constexpr int MLP_COLS = 32;
constexpr int MLP_CTAS = FF / MLP_COLS;
constexpr int OUT_COLS = D_MODEL / NCTA;
constexpr int NTHREADS = 320;
#define OP_SLEEP 200
#define GATE_SLACK 8

constexpr int OFF_RING = 0;
constexpr int OFF_WO = OFF_RING + STAGES * TILE_BYTES;
constexpr int OFF_SC = OFF_WO + WO_BYTES;
constexpr int OFF_XN = OFF_SC + KEYS_PER_CTA * 4;
constexpr int OFF_Y = OFF_XN + D_MODEL * 4;
constexpr int OFF_RED = OFF_Y + D_MODEL * 4;
constexpr int OFF_Q = OFF_RED + 8 * DH * 4;
constexpr int OFF_MISC = OFF_Q + DH * 4;
constexpr int OFF_BAR = OFF_MISC + 256;
constexpr int SMEM_BYTES = OFF_BAR + (2 * STAGES + 1) * 8;

struct alignas(256) Scratch {
    uint32_t q[NHEAD * DH];
    unsigned long long ml[NCTA];
    uint2 op[NCTA * DH];
    uint2 outA[NCTA * D_MODEL];
    float accB[D_MODEL];
    unsigned int cntB;
    unsigned int prog;
    unsigned int arrive;
};
__device__ Scratch g_scr[1];

#define TL(i) do { } while (0)
#define TLE(i) do { } while (0)

__device__ __forceinline__ uint32_t s2u(const void* p) { return (uint32_t)__cvta_generic_to_shared(p); }
__device__ __forceinline__ void mbar_init(uint32_t a, uint32_t c) {
    asm volatile("mbarrier.init.shared::cta.b64 [%0], %1;" ::"r"(a), "r"(c));
}
__device__ __forceinline__ void mbar_expect(uint32_t a, uint32_t b) {
    asm volatile("mbarrier.arrive.expect_tx.shared::cta.b64 _, [%0], %1;" ::"r"(a), "r"(b) : "memory");
}
__device__ __forceinline__ void mbar_arrive(uint32_t a) {
    asm volatile("mbarrier.arrive.shared::cta.b64 _, [%0];" ::"r"(a) : "memory");
}
__device__ __forceinline__ void mbar_wait(uint32_t a, uint32_t ph) {
    uint32_t ok;
    int it = 0;
    do {
        asm volatile(
            "{\n.reg .pred p;\nmbarrier.try_wait.parity.shared::cta.b64 p, [%1], %2;\nselp.u32 %0,1,0,p;\n}"
            : "=r"(ok)
            : "r"(a), "r"(ph)
            : "memory");
        if (++it > (1 << 22)) __trap();
    } while (!ok);
}
__device__ __forceinline__ void bulk_g2s(uint32_t dst, const void* src, uint32_t bytes, uint32_t bar) {
    asm volatile("cp.async.bulk.shared::cluster.global.mbarrier::complete_tx::bytes [%0], [%1], %2, [%3];" ::"r"(dst),
                 "l"(src), "r"(bytes), "r"(bar)
                 : "memory");
}
__device__ __forceinline__ void cbar() { asm volatile("bar.sync 1, 256;" ::: "memory"); }

__device__ __forceinline__ float bfr(float x) { return __bfloat162float(__float2bfloat16_rn(x)); }
__device__ __forceinline__ float bflo(uint32_t u) { return __uint_as_float(u << 16); }
__device__ __forceinline__ float bfhi(uint32_t u) { return __uint_as_float(u & 0xffff0000u); }
__device__ __forceinline__ float ex2(float x) {
    float r;
    asm("ex2.approx.ftz.f32 %0, %1;" : "=f"(r) : "f"(x));
    return r;
}

__device__ __forceinline__ uint4 ldg_nc16(const void* p) {
    uint4 v;
    asm volatile("ld.global.nc.L1::no_allocate.v4.u32 {%0,%1,%2,%3}, [%4];"
                 : "=r"(v.x), "=r"(v.y), "=r"(v.z), "=r"(v.w)
                 : "l"(p));
    return v;
}
__device__ __forceinline__ uint2 ldg_nc8(const void* p) {
    uint2 v;
    asm volatile("ld.global.nc.L1::no_allocate.v2.u32 {%0,%1}, [%2];" : "=r"(v.x), "=r"(v.y) : "l"(p));
    return v;
}
__device__ __forceinline__ void st_tagged(uint2* p, float v) {
    asm volatile("st.relaxed.gpu.global.v2.u32 [%0], {%1, %2};" ::"l"(p), "r"(__float_as_uint(v)), "r"(1u) : "memory");
}
__device__ __forceinline__ float take_tagged(uint2* p) {
    uint32_t v, t;
    int it = 0;
    do {
        asm volatile("ld.relaxed.gpu.global.v2.u32 {%0, %1}, [%2];" : "=r"(v), "=r"(t) : "l"(p) : "memory");
        if (++it > (1 << 24)) __trap();
    } while (t == 0u);
    asm volatile("st.relaxed.gpu.global.v2.u32 [%0], {%1, %1};" ::"l"(p), "r"(0u) : "memory");
    return __uint_as_float(v);
}
__device__ __forceinline__ float warp_sum(float v) {
#pragma unroll
    for (int o = 16; o > 0; o >>= 1) v += __shfl_xor_sync(0xffffffffu, v, o);
    return v;
}

__device__ __forceinline__ void fma8(float* acc, float s, const uint4& v) {
    acc[0] = fmaf(s, bflo(v.x), acc[0]);
    acc[1] = fmaf(s, bfhi(v.x), acc[1]);
    acc[2] = fmaf(s, bflo(v.y), acc[2]);
    acc[3] = fmaf(s, bfhi(v.y), acc[3]);
    acc[4] = fmaf(s, bflo(v.z), acc[4]);
    acc[5] = fmaf(s, bfhi(v.z), acc[5]);
    acc[6] = fmaf(s, bflo(v.w), acc[6]);
    acc[7] = fmaf(s, bfhi(v.w), acc[7]);
}
__device__ __forceinline__ float dot8(const float* q, const uint4& v) {
    float a = q[0] * bflo(v.x);
    float b = q[1] * bfhi(v.x);
    a = fmaf(q[2], bflo(v.y), a);
    b = fmaf(q[3], bfhi(v.y), b);
    a = fmaf(q[4], bflo(v.z), a);
    b = fmaf(q[5], bfhi(v.z), b);
    a = fmaf(q[6], bflo(v.w), a);
    b = fmaf(q[7], bfhi(v.w), b);
    return a + b;
}

__device__ __noinline__ void warp_layernorm(float* v) {
    float s = 0.f;
#pragma unroll
    for (int i = 0; i < 20; i++) s += v[i];
    s = warp_sum(s);
    const float mean = s * (1.0f / D_MODEL);
    float ss = 0.f;
#pragma unroll
    for (int i = 0; i < 20; i++) {
        float d = v[i] - mean;
        ss = fmaf(d, d, ss);
    }
    ss = warp_sum(ss);
    const float m_bf = bfr(mean);
    const float v_bf = bfr(ss * (1.0f / D_MODEL));
    const float den = bfr(sqrtf(bfr(v_bf + 1e-5f)));
#pragma unroll
    for (int i = 0; i < 20; i++) v[i] = bfr(__fdiv_rn(bfr(v[i] - m_bf), den));
}

constexpr float L2E = 1.4426950408889634f;

__device__ __forceinline__ void ml_merge(float& m, float& l, int o) {
    const float mo = __shfl_xor_sync(0xffffffffu, m, o);
    const float lo = __shfl_xor_sync(0xffffffffu, l, o);
    const float mn = fmaxf(m, mo);
    l = l * ex2((m - mn) * L2E) + lo * ex2((mo - mn) * L2E);
    m = mn;
}

__device__ __forceinline__ void mid_phase(int tid, int cta, Scratch* g, float* misc, float mrun, float lrun) {
    const int warp = tid >> 5, lane = tid & 31;
    if (lane & 3) lrun = 0.f;
#pragma unroll 1
    for (int o = 16; o > 0; o >>= 1) ml_merge(mrun, lrun, o);
    if (lane == 0) { misc[16 + warp] = mrun; misc[24 + warp] = lrun; }
    cbar();
    if (warp == 0) {
        float m = (lane < 8) ? misc[16 + lane] : -INFINITY;
        float l = (lane < 8) ? misc[24 + lane] : 0.f;
#pragma unroll 1
        for (int o = 4; o > 0; o >>= 1) ml_merge(m, l, o);
        if (lane == 0) {
            unsigned long long pk = ((unsigned long long)__float_as_uint(l) << 32) | __float_as_uint(m);
            asm volatile("st.relaxed.gpu.global.u64 [%0], %1;" ::"l"(&g->ml[cta]), "l"(pk) : "memory");
        }
        m = -INFINITY;
        l = 0.f;
        if (lane < NSPLIT) {
            unsigned long long pk;
            int it = 0;
            do {
                asm volatile("ld.relaxed.gpu.global.u64 %0, [%1];" : "=l"(pk) : "l"(&g->ml[(cta & ~3) + lane]) : "memory");
                if (++it > (1 << 24)) __trap();
            } while ((pk >> 32) == 0ull);
            m = __uint_as_float((uint32_t)pk);
            l = __uint_as_float((uint32_t)(pk >> 32));
        }
#pragma unroll 1
        for (int o = 2; o > 0; o >>= 1) ml_merge(m, l, o);
        if (lane == 0) { misc[32] = m; misc[33] = __fdiv_rn(1.0f, l); }
        asm volatile("st.relaxed.gpu.global.u32 [%0], %1;" ::"l"(&g->q[cta * WO_ROWS + lane]), "r"(0u) : "memory");
    }
    cbar();
}

__device__ __forceinline__ void epilogue(int tid, int cta, Scratch* g, float* red, float* q_s, float* misc,
                                         const unsigned char* wo_s, uint32_t bar_wo, unsigned int arrive_base, float xcol,
                                         __nv_bfloat16* out, float* oa) {
    const int warp = tid >> 5, lane = tid & 31;
#pragma unroll
    for (int i = 0; i < 8; i++) oa[i] += __shfl_xor_sync(0xffffffffu, oa[i], 16);
    if (lane < 16) {
        *reinterpret_cast<float4*>(&red[warp * DH + lane * 8]) = make_float4(oa[0], oa[1], oa[2], oa[3]);
        *reinterpret_cast<float4*>(&red[warp * DH + lane * 8 + 4]) = make_float4(oa[4], oa[5], oa[6], oa[7]);
    }
    cbar();
    if (tid < DH) {
        float v = 0.f;
#pragma unroll
        for (int w = 0; w < 8; w++) v += red[w * DH + tid];
        st_tagged(&g->op[cta * DH + tid], v);
    }
    uint2* opw = &g->op[(cta & ~3) * DH + (cta & 3) * WO_ROWS + lane];
    if (warp == 0) {
        float v[NSPLIT];
        int it = 0;
        while (true) {
            uint32_t tg = 1u;
#pragma unroll
            for (int j = 0; j < NSPLIT; j++) {
                uint32_t vv, t;
                asm volatile("ld.relaxed.gpu.global.v2.u32 {%0, %1}, [%2];" : "=r"(vv), "=r"(t) : "l"(opw + j * DH) : "memory");
                v[j] = __uint_as_float(vv);
                tg &= t;
            }
            if (tg) break;
            __nanosleep(OP_SLEEP);
            if (++it > (1 << 22)) __trap();
        }
        q_s[lane] = bfr((v[0] + v[1]) + (v[2] + v[3]));
    }
    mbar_wait(bar_wo, 0);
    cbar();
    TL(5);
    if (tid < 160) {
        float a0 = 0.f, a1 = 0.f, a2 = 0.f, a3 = 0.f;
        const unsigned char* wp = wo_s + tid * 8;
#pragma unroll 1
        for (int r4 = 0; r4 < WO_ROWS / 4; r4++) {
            const float4 ov = *reinterpret_cast<const float4*>(&q_s[r4 * 4]);
            const float ovv[4] = {ov.x, ov.y, ov.z, ov.w};
#pragma unroll
            for (int k = 0; k < 4; k++) {
                const uint2 w = *reinterpret_cast<const uint2*>(wp + (r4 * 4 + k) * (D_MODEL * 2));
                a0 = fmaf(ovv[k], bflo(w.x), a0);
                a1 = fmaf(ovv[k], bfhi(w.x), a1);
                a2 = fmaf(ovv[k], bflo(w.y), a2);
                a3 = fmaf(ovv[k], bfhi(w.y), a3);
            }
        }
        uint2* dst = &g->outA[cta * D_MODEL + tid * 4];
        asm volatile("st.relaxed.gpu.global.v4.u32 [%0], {%1, %2, %3, %2};" ::"l"(dst), "r"(__float_as_uint(a0)), "r"(1u),
                     "r"(__float_as_uint(a1))
                     : "memory");
        asm volatile("st.relaxed.gpu.global.v4.u32 [%0], {%1, %2, %3, %2};" ::"l"(dst + 2), "r"(__float_as_uint(a2)), "r"(1u),
                     "r"(__float_as_uint(a3))
                     : "memory");
    }
    if (tid == 255) asm volatile("red.relaxed.gpu.global.add.u32 [%0], %1;" ::"l"(&g->arrive), "r"(1u) : "memory");
    TL(6);
    uint2* src = &g->outA[(tid & (NCTA - 1)) * D_MODEL + cta * OUT_COLS];
    {
        uint32_t ok = tid < NCTA ? 0u : 1u;
        int it = 0;
        while (true) {
            if (!ok) {
                uint32_t tg = 1u;
#pragma unroll
                for (int k = 0; k < OUT_COLS; k++) {
                    uint32_t vv, t;
                    asm volatile("ld.relaxed.gpu.global.v2.u32 {%0, %1}, [%2];" : "=r"(vv), "=r"(t) : "l"(src + k) : "memory");
                    red[k * NCTA + tid] = __uint_as_float(vv);
                    tg &= t;
                }
                ok = tg;
            }
            uint32_t all;
            asm volatile(
                "{\n.reg .pred p, q;\nsetp.ne.u32 p, %1, 0;\nbar.red.and.pred q, 1, 256, p;\nselp.u32 %0, 1, 0, q;\n}"
                : "=r"(all)
                : "r"(ok)
                : "memory");
            if (all) break;
            if (tid == 0) {
                unsigned int cnt;
                int it2 = 0;
                while (true) {
                    asm volatile("ld.relaxed.gpu.global.u32 %0, [%1];" : "=r"(cnt) : "l"(&g->arrive) : "memory");
                    if (cnt - arrive_base >= (unsigned)(NCTA - GATE_SLACK)) break;
                    __nanosleep(100);
                    if (++it2 > (1 << 22)) __trap();
                }
            }
            cbar();
            if (++it > (1 << 22)) __trap();
        }
    }
    TL(10);
    asm volatile("bar.sync 3, 288;" ::: "memory");
    if (warp < OUT_COLS) {
        const float* rp = red + warp * NCTA + lane;
        const float a = bfr(warp_sum((rp[0] + rp[32]) + (rp[64] + rp[96])));
        if (lane == 0) out[cta * OUT_COLS + warp] = __float2bfloat16_rn(bfr(xcol + a) + misc[40 + warp]);
    }
    TL(11);
    if (tid < NCTA) {
#pragma unroll
        for (int k = 0; k < OUT_COLS; k++)
            asm volatile("st.relaxed.gpu.global.v2.u32 [%0], {%1, %1};" ::"l"(src + k), "r"(0u) : "memory");
    }
    if (warp == 0) {
#pragma unroll
        for (int j = 0; j < NSPLIT; j++)
            asm volatile("st.relaxed.gpu.global.v2.u32 [%0], {%1, %1};" ::"l"(opw + j * DH), "r"(0u) : "memory");
        if (lane == 0) asm volatile("st.relaxed.gpu.global.u64 [%0], %1;" ::"l"(&g->ml[cta]), "l"(0ull) : "memory");
    }
}

__global__ void __launch_bounds__(NTHREADS, 1)
fused_decode_kernel(const __nv_bfloat16* __restrict__ x, const __nv_bfloat16* __restrict__ kc,
                    const __nv_bfloat16* __restrict__ vc, const __nv_bfloat16* __restrict__ wq,
                    const __nv_bfloat16* __restrict__ wo, const __nv_bfloat16* __restrict__ w1,
                    const __nv_bfloat16* __restrict__ b1, const __nv_bfloat16* __restrict__ w2,
                    const __nv_bfloat16* __restrict__ b2, __nv_bfloat16* __restrict__ out) {
    extern __shared__ __align__(1024) unsigned char smem[];
    const int tid = threadIdx.x, warp = tid >> 5, lane = tid & 31;
    const int cta = blockIdx.x, head = cta >> 2, split = cta & 3;

    float* sc = reinterpret_cast<float*>(smem + OFF_SC);
    float* xn_s = reinterpret_cast<float*>(smem + OFF_XN);
    float* q_s = reinterpret_cast<float*>(smem + OFF_Q);
    float* red = reinterpret_cast<float*>(smem + OFF_RED);
    float* misc = reinterpret_cast<float*>(smem + OFF_MISC);
    const uint32_t bar_full = s2u(smem + OFF_BAR);
    const uint32_t bar_empty = bar_full + STAGES * 8;
    const uint32_t bar_wo = bar_full + 2 * STAGES * 8;

    TL(0);
    if (warp == 8) {
        if (lane < 2 * STAGES + 1) mbar_init(bar_full + lane * 8, (lane >= STAGES && lane < 2 * STAGES) ? 8 : 1);
        asm volatile("fence.mbarrier_init.release.cluster;" ::: "memory");
    } else if (warp < 8) {
        const unsigned char* wqp = reinterpret_cast<const unsigned char*>(wq) + (size_t)(head * DH + split * WO_ROWS) * 2 +
                                   (tid & 3) * 16 + (size_t)(tid >> 2) * (NHEAD * DH * 2);
        uint32_t dst = s2u(smem + OFF_WO) + tid * 16;
#pragma unroll 1
        for (int i = 0; i < 10; i++) {
            asm volatile("cp.async.cg.shared.global [%0], [%1], 16;" ::"r"(dst), "l"(wqp) : "memory");
            dst += 4096;
            wqp += (size_t)64 * (NHEAD * DH * 2);
        }
        asm volatile("cp.async.commit_group;" ::: "memory");
    }
    __syncthreads();

    if (warp == 8) {
        if (lane == 0) {
            const unsigned char* kbase =
                reinterpret_cast<const unsigned char*>(kc) + (size_t)head * SK * (DH * 2) + (size_t)split * TILE_BYTES;
            const unsigned char* vbase =
                reinterpret_cast<const unsigned char*>(vc) + (size_t)head * SK * (DH * 2) + (size_t)split * TILE_BYTES;
            const uint32_t ring = s2u(smem + OFF_RING);
            int s = 0, landed = 0;
            uint32_t ph = 1;
#pragma unroll 1
            for (int t = 0; t < 2 * NT; t++) {
                int depth = INFLIGHT;
                while (landed <= t - depth) {
                    mbar_wait(bar_full + (landed % STAGES) * 8, (landed / STAGES) & 1);
                    landed++;
                }
                mbar_wait(bar_empty + s * 8, ph);
                mbar_expect(bar_full + s * 8, TILE_BYTES);
                const unsigned char* src =
                    (t < NT) ? (kbase + (size_t)t * (NSPLIT * TILE_BYTES)) : (vbase + (size_t)(t - NT) * (NSPLIT * TILE_BYTES));
                bulk_g2s(ring + s * TILE_BYTES, src, TILE_BYTES, bar_full + s * 8);
                if (t == STAGES) {
                    mbar_expect(bar_wo, WO_BYTES);
                    bulk_g2s(s2u(smem + OFF_WO),
                             reinterpret_cast<const unsigned char*>(wo) + (size_t)(head * DH + split * WO_ROWS) * (D_MODEL * 2),
                             WO_BYTES, bar_wo);
                }
                if (++s == STAGES) { s = 0; ph ^= 1; }
            }
        }
    } else if (warp == 9) {
        unsigned int bbase;
        asm volatile("ld.relaxed.gpu.global.u32 %0, [%1];" : "=r"(bbase) : "l"(&g_scr[0].cntB) : "memory");
        bbase &= ~(unsigned)(NCTA - 1);
        if (cta < MLP_CTAS) {
            const int f0 = cta * MLP_COLS;
            float* y_s = reinterpret_cast<float*>(smem + OFF_Y);
            {
                float v[20];
#pragma unroll
                for (int i = 0; i < 20; i++) v[i] = __bfloat162float(x[lane + 32 * i]);
                warp_layernorm(v);
                warp_layernorm(v);
#pragma unroll
                for (int i = 0; i < 20; i++) y_s[lane + 32 * i] = v[i];
            }
            __syncwarp();
            float acc[8];
#pragma unroll
            for (int i = 0; i < 8; i++) acc[i] = 0.f;
            const unsigned char* w1p =
                reinterpret_cast<const unsigned char*>(w1) + (size_t)f0 * 2 + (lane & 3) * 16 + (size_t)(lane >> 2) * (FF * 2);
#pragma unroll 1
            for (int b = 0; b < 8; b++) {
                uint4 wv[10];
#pragma unroll
                for (int i = 0; i < 10; i++) wv[i] = ldg_nc16(w1p + (size_t)((b * 10 + i) * 8) * (FF * 2));
#pragma unroll
                for (int i = 0; i < 10; i++) fma8(acc, y_s[(b * 10 + i) * 8 + (lane >> 2)], wv[i]);
            }
#pragma unroll
            for (int i = 0; i < 8; i++) {
#pragma unroll
                for (int o = 4; o <= 16; o <<= 1) acc[i] += __shfl_xor_sync(0xffffffffu, acc[i], o);
            }
            float hval[8];
#pragma unroll
            for (int i = 0; i < 8; i++) {
                const int f = f0 + (lane & 3) * 8 + i;
                const float pre = bfr(bfr(acc[i]) + __bfloat162float(b1[f]));
                const float inner = 0.7978845608028654f * (pre + 0.044715f * pre * pre * pre);
                hval[i] = bfr(0.5f * pre * (1.0f + tanhf(inner)));
            }
            float o[20];
#pragma unroll
            for (int i = 0; i < 20; i++) o[i] = 0.f;
            const unsigned char* w2p = reinterpret_cast<const unsigned char*>(w2) + (size_t)f0 * (D_MODEL * 2) + lane * 8;
#pragma unroll 1
            for (int rb = 0; rb < 4; rb++) {
                uint2 wv[8][5];
#pragma unroll
                for (int r = 0; r < 8; r++)
#pragma unroll
                    for (int i = 0; i < 5; i++) wv[r][i] = ldg_nc8(w2p + (size_t)(rb * 8 + r) * (D_MODEL * 2) + i * 256);
#pragma unroll
                for (int r = 0; r < 8; r++) {
                    const float hv = __shfl_sync(0xffffffffu, hval[r], rb);
#pragma unroll
                    for (int i = 0; i < 5; i++) {
                        o[i * 4 + 0] = fmaf(hv, bflo(wv[r][i].x), o[i * 4 + 0]);
                        o[i * 4 + 1] = fmaf(hv, bfhi(wv[r][i].x), o[i * 4 + 1]);
                        o[i * 4 + 2] = fmaf(hv, bflo(wv[r][i].y), o[i * 4 + 2]);
                        o[i * 4 + 3] = fmaf(hv, bfhi(wv[r][i].y), o[i * 4 + 3]);
                    }
                }
            }
#pragma unroll
            for (int i = 0; i < 5; i++)
#pragma unroll
                for (int j = 0; j < 4; j++) atomicAdd(&g_scr[0].accB[(lane + 32 * i) * 4 + j], o[i * 4 + j]);
            __threadfence();
            __syncwarp();
        }
        if (lane == 0) atomicAdd(&g_scr[0].cntB, 1u);
        {
            mbar_wait(bar_empty + (STAGES - 1) * 8, 0);
            mbar_wait(bar_empty + (STAGES - 1) * 8, 1);
            if (lane < OUT_COLS) {
                unsigned int c;
                int it = 0;
                while (true) {
                    asm volatile("ld.acquire.gpu.global.u32 %0, [%1];" : "=r"(c) : "l"(&g_scr[0].cntB) : "memory");
                    if (c - bbase >= (unsigned)NCTA) break;
                    __nanosleep(1000);
                    if (++it > (1 << 22)) __trap();
                }
                float* ap = &g_scr[0].accB[cta * OUT_COLS + lane];
                const float b = __ldcg(ap);
                __stcg(ap, 0.f);
                misc[40 + lane] = bfr(bfr(b) + __bfloat162float(b2[cta * OUT_COLS + lane]));
            }
            __syncwarp();
            asm volatile("bar.arrive 3, 288;" ::: "memory");
        }
    } else {
        unsigned int arrive_base = 0;
        if (tid == 0) {
            asm volatile("ld.relaxed.gpu.global.u32 %0, [%1];" : "=r"(arrive_base) : "l"(&g_scr[0].arrive) : "memory");
            arrive_base &= ~(unsigned)(NCTA - 1);
        }
        float xcol = 0.f;
        if (lane == 0 && warp < OUT_COLS) xcol = __bfloat162float(x[cta * OUT_COLS + warp]);
        float xv[3];
#pragma unroll
        for (int j = 0; j < 3; j++) xv[j] = (tid + 256 * j < D_MODEL) ? __bfloat162float(x[tid + 256 * j]) : 0.f;
        {
            float s = warp_sum(xv[0] + xv[1] + xv[2]);
            if (lane == 0) misc[warp] = s;
            cbar();
            float tot = 0.f;
#pragma unroll
            for (int w = 0; w < 8; w++) tot += misc[w];
            const float mean = tot * (1.0f / D_MODEL);
            float ss = 0.f;
#pragma unroll
            for (int j = 0; j < 3; j++) {
                const float d = (tid + 256 * j < D_MODEL) ? xv[j] - mean : 0.f;
                ss = fmaf(d, d, ss);
            }
            ss = warp_sum(ss);
            if (lane == 0) misc[8 + warp] = ss;
            cbar();
            float tss = 0.f;
#pragma unroll
            for (int w = 0; w < 8; w++) tss += misc[8 + w];
            const float m_bf = bfr(mean);
            const float v_bf = bfr(tss * (1.0f / D_MODEL));
            const float den = bfr(__fsqrt_rn(bfr(v_bf + 1e-5f)));
#pragma unroll 1
            for (int j = 0; j < 3; j++) {
                const float xj = j == 0 ? xv[0] : (j == 1 ? xv[1] : xv[2]);
                if (tid + 256 * j < D_MODEL) xn_s[tid + 256 * j] = bfr(__fdiv_rn(bfr(xj - m_bf), den));
            }
        }
        asm volatile("cp.async.wait_all;" ::: "memory");
        cbar();
        TL(8);
        {
            float qa[8];
#pragma unroll
            for (int i = 0; i < 8; i++) qa[i] = 0.f;
            const unsigned char* wp = smem + OFF_WO + tid * 16;
#pragma unroll 2
            for (int i = 0; i < 10; i++)
                fma8(qa, xn_s[i * 64 + (tid >> 2)], *reinterpret_cast<const uint4*>(wp + i * 4096));
#pragma unroll
            for (int i = 0; i < 8; i++) {
                qa[i] += __shfl_xor_sync(0xffffffffu, qa[i], 4);
                qa[i] += __shfl_xor_sync(0xffffffffu, qa[i], 8);
                qa[i] += __shfl_xor_sync(0xffffffffu, qa[i], 16);
            }
            if (lane < 4) {
                *reinterpret_cast<float4*>(&red[warp * 32 + lane * 8]) = make_float4(qa[0], qa[1], qa[2], qa[3]);
                *reinterpret_cast<float4*>(&red[warp * 32 + lane * 8 + 4]) = make_float4(qa[4], qa[5], qa[6], qa[7]);
            }
        }
        cbar();
        if (tid < 32) {
            float s = 0.f;
#pragma unroll
            for (int w = 0; w < 8; w++) s += red[w * 32 + tid];
            const uint32_t wrd = (__float_as_uint(bfr(s)) & 0xffff0000u) | 1u;
            asm volatile("st.relaxed.gpu.global.u32 [%0], %1;" ::"l"(&g_scr[0].q[head * DH + split * WO_ROWS + tid]), "r"(wrd) : "memory");
        }
        if (warp == 0) {
            uint32_t w0, w1_, w2_, w3;
            int it = 0;
            while (true) {
                asm volatile("ld.relaxed.gpu.global.v4.u32 {%0,%1,%2,%3}, [%4];"
                             : "=r"(w0), "=r"(w1_), "=r"(w2_), "=r"(w3)
                             : "l"(&g_scr[0].q[head * DH + lane * 4])
                             : "memory");
                if (w0 & w1_ & w2_ & w3 & 1u) break;
                __nanosleep(40);
                if (++it > (1 << 22)) __trap();
            }
            *reinterpret_cast<uint4*>(&q_s[lane * 4]) =
                make_uint4(w0 & 0xffff0000u, w1_ & 0xffff0000u, w2_ & 0xffff0000u, w3 & 0xffff0000u);
        }
        cbar();
        float q[8];
        {
            const float4 qa = *reinterpret_cast<const float4*>(&q_s[(lane & 15) * 8]);
            const float4 qb = *reinterpret_cast<const float4*>(&q_s[(lane & 15) * 8 + 4]);
            q[0] = qa.x; q[1] = qa.y; q[2] = qa.z; q[3] = qa.w;
            q[4] = qb.x; q[5] = qb.y; q[6] = qb.z; q[7] = qb.w;
        }

        TL(1);
        const float scale = 0.08838834764831845f;
        const unsigned char* ring = smem + OFF_RING;
        int s = 0;
        uint32_t ph = 0;
        float mrun = -INFINITY, lrun = 0.f;
        const int lane_off = (warp * 8 + (lane >> 4)) * (DH * 2) + (lane & 15) * 16;
        const bool l3 = lane & 8, l2 = lane & 4;
        const int key_off = warp * 8 + 2 * ((l3 ? 2 : 0) + (l2 ? 1 : 0)) + (lane >> 4);
#pragma unroll 1
        for (int t = 0; t < NT; t++) {
            mbar_wait(bar_full + s * 8, ph);
            const unsigned char* tp = ring + s * TILE_BYTES + lane_off;
            uint4 kv[4];
#pragma unroll
            for (int j = 0; j < 4; j++) kv[j] = *reinterpret_cast<const uint4*>(tp + j * 2 * (DH * 2));
            float a0 = dot8(q, kv[0]), a1 = dot8(q, kv[1]), a2 = dot8(q, kv[2]), a3 = dot8(q, kv[3]);
            __syncwarp();
            if (lane == 0) mbar_arrive(bar_empty + s * 8);
            float s0 = l3 ? a0 : a2, s1 = l3 ? a1 : a3;
            float k0 = l3 ? a2 : a0, k1 = l3 ? a3 : a1;
            k0 += __shfl_xor_sync(0xffffffffu, s0, 8);
            k1 += __shfl_xor_sync(0xffffffffu, s1, 8);
            float sn = l2 ? k0 : k1, kp = l2 ? k1 : k0;
            kp += __shfl_xor_sync(0xffffffffu, sn, 4);
            kp += __shfl_xor_sync(0xffffffffu, kp, 2);
            kp += __shfl_xor_sync(0xffffffffu, kp, 1);
            const float sv = bfr(bfr(kp) * scale);
            const float mnew = fmaxf(mrun, sv);
            lrun = lrun * ex2((mrun - mnew) * L2E) + ex2((sv - mnew) * L2E);
            mrun = mnew;
            if ((lane & 3) == 0) sc[t * TILE + key_off] = sv;
            if (++s == STAGES) { s = 0; ph ^= 1; }
        }

        TL(2);
        mid_phase(tid, cta, &g_scr[0], misc, mrun, lrun);
        const float mg = misc[32], inv_l = misc[33];

        TL(3);
        float oa[8];
#pragma unroll
        for (int i = 0; i < 8; i++) oa[i] = 0.f;
        const int pkey = warp * 8 + (lane >> 4);
#pragma unroll 1
        for (int t = 0; t < NT; t++) {
            float p[4];
#pragma unroll
            for (int j = 0; j < 4; j++) p[j] = bfr(ex2((sc[t * TILE + pkey + 2 * j] - mg) * L2E) * inv_l);
            mbar_wait(bar_full + s * 8, ph);
            const unsigned char* tp = ring + s * TILE_BYTES + lane_off;
            uint4 vv[4];
#pragma unroll
            for (int j = 0; j < 4; j++) vv[j] = *reinterpret_cast<const uint4*>(tp + j * 2 * (DH * 2));
#pragma unroll
            for (int j = 0; j < 4; j++) fma8(oa, p[j], vv[j]);
            __syncwarp();
            if (lane == 0) mbar_arrive(bar_empty + s * 8);
            if (++s == STAGES) { s = 0; ph ^= 1; }
        }
        TL(4);
        epilogue(tid, cta, &g_scr[0], red, q_s, misc, smem + OFF_WO, bar_wo, arrive_base, xcol, out, oa);
        TL(7);
    }
}

}

extern "C" void kernel_launch(void* const* d_in, const int* in_sizes, int n_in, void* d_out, int out_size) {
    const __nv_bfloat16* x = (const __nv_bfloat16*)d_in[0];
    const __nv_bfloat16* kc = (const __nv_bfloat16*)d_in[1];
    const __nv_bfloat16* vc = (const __nv_bfloat16*)d_in[2];
    const __nv_bfloat16* wq = (const __nv_bfloat16*)d_in[3];
    const __nv_bfloat16* wo = (const __nv_bfloat16*)d_in[4];
    const __nv_bfloat16* w1 = (const __nv_bfloat16*)d_in[6];
    const __nv_bfloat16* b1 = (const __nv_bfloat16*)d_in[7];
    const __nv_bfloat16* w2 = (const __nv_bfloat16*)d_in[8];
    const __nv_bfloat16* b2 = (const __nv_bfloat16*)d_in[9];
    static bool attr_set = false;
    if (!attr_set) {
        cudaFuncSetAttribute(fused_decode_kernel, cudaFuncAttributeMaxDynamicSharedMemorySize, SMEM_BYTES);
        attr_set = true;
    }
    fused_decode_kernel<<<NCTA, NTHREADS, SMEM_BYTES>>>(x, kc, vc, wq, wo, w1, b1, w2, b2, (__nv_bfloat16*)d_out);
}
```

```cpp
#include <cuda_runtime.h>
#include <cuda_bf16.h>
#include <stdint.h>

namespace {

constexpr int D_MODEL = 640;
constexpr int NHEAD = 32;
constexpr int SK = 16384;
constexpr int DH = 128;
constexpr int FF = 1728;
constexpr int NSPLIT = 4;
constexpr int NCTA = NHEAD * NSPLIT;
constexpr int KEYS_PER_CTA = SK / NSPLIT;
constexpr int TILE = 64;
constexpr int TILE_BYTES = TILE * DH * 2;
constexpr int NT = KEYS_PER_CTA / TILE;
constexpr int STAGES = 10;
#define INFLIGHT_N 4
constexpr int INFLIGHT = INFLIGHT_N;
constexpr int WO_ROWS = DH / NSPLIT;
constexpr int WO_BYTES = WO_ROWS * D_MODEL * 2;
constexpr int MLP_COLS = 32;
constexpr int MLP_CTAS = FF / MLP_COLS;
constexpr int OUT_COLS = D_MODEL / NCTA;
constexpr int NTHREADS = 320;
#define GATE_SLACK 4

constexpr int OFF_RING = 0;
constexpr int OFF_WO = OFF_RING + STAGES * TILE_BYTES;
constexpr int OFF_SC = OFF_WO + WO_BYTES;
constexpr int OFF_XN = OFF_SC + KEYS_PER_CTA * 4;
constexpr int OFF_Y = OFF_XN + D_MODEL * 4;
constexpr int OFF_RED = OFF_Y + D_MODEL * 4;
constexpr int OFF_Q = OFF_RED + 8 * DH * 4;
constexpr int OFF_MISC = OFF_Q + DH * 4;
constexpr int OFF_BAR = OFF_MISC + 256;
constexpr int SMEM_BYTES = OFF_BAR + (2 * STAGES + 1) * 8;

struct alignas(256) Scratch {
    uint32_t q[NHEAD * DH];
    unsigned long long ml[NCTA];
    unsigned long long op[NCTA * DH];
    unsigned long long outA[NCTA * D_MODEL];
    float accB[D_MODEL];
    unsigned int cntB;
    unsigned int arrive;
};
__device__ Scratch g_scr;

#define TL(i) do { } while (0)

__device__ __forceinline__ uint32_t s2u(const void* p) { return (uint32_t)__cvta_generic_to_shared(p); }
__device__ __forceinline__ void mbar_init(uint32_t a, uint32_t c) {
    asm volatile("mbarrier.init.shared::cta.b64 [%0], %1;" ::"r"(a), "r"(c));
}
__device__ __forceinline__ void mbar_expect(uint32_t a, uint32_t b) {
    asm volatile("mbarrier.arrive.expect_tx.shared::cta.b64 _, [%0], %1;" ::"r"(a), "r"(b) : "memory");
}
__device__ __forceinline__ void mbar_arrive(uint32_t a) {
    asm volatile("mbarrier.arrive.shared::cta.b64 _, [%0];" ::"r"(a) : "memory");
}
__device__ __forceinline__ void mbar_wait(uint32_t a, uint32_t ph) {
    uint32_t ok;
    int it = 0;
    do {
        asm volatile(
            "{\n.reg .pred p;\nmbarrier.try_wait.parity.shared::cta.b64 p, [%1], %2;\nselp.u32 %0,1,0,p;\n}"
            : "=r"(ok)
            : "r"(a), "r"(ph)
            : "memory");
        if (++it > (1 << 22)) __trap();
    } while (!ok);
}
__device__ __forceinline__ void bulk_g2s(uint32_t dst, const void* src, uint32_t bytes, uint32_t bar) {
    asm volatile("cp.async.bulk.shared::cluster.global.mbarrier::complete_tx::bytes [%0], [%1], %2, [%3];" ::"r"(dst),
                 "l"(src), "r"(bytes), "r"(bar)
                 : "memory");
}
__device__ __forceinline__ void bulk_g2s_hint(uint32_t dst, const void* src, uint32_t bytes, uint32_t bar, uint64_t pol) {
    asm volatile("cp.async.bulk.shared::cluster.global.mbarrier::complete_tx::bytes.L2::cache_hint [%0], [%1], %2, [%3], %4;" ::"r"(dst),
                 "l"(src), "r"(bytes), "r"(bar), "l"(pol)
                 : "memory");
}
__device__ __forceinline__ void cbar() { asm volatile("bar.sync 1, 256;" ::: "memory"); }

__device__ __forceinline__ float bfr(float x) { return __bfloat162float(__float2bfloat16_rn(x)); }
__device__ __forceinline__ float bflo(uint32_t u) { return __uint_as_float(u << 16); }
__device__ __forceinline__ float bfhi(uint32_t u) { return __uint_as_float(u & 0xffff0000u); }
__device__ __forceinline__ float ex2(float x) {
    float r;
    asm("ex2.approx.ftz.f32 %0, %1;" : "=f"(r) : "f"(x));
    return r;
}

__device__ __forceinline__ uint4 ldg_nc16(const void* p) {
    uint4 v;
    asm volatile("ld.global.nc.L1::no_allocate.v4.u32 {%0,%1,%2,%3}, [%4];"
                 : "=r"(v.x), "=r"(v.y), "=r"(v.z), "=r"(v.w)
                 : "l"(p));
    return v;
}
__device__ __forceinline__ uint2 ldg_nc8(const void* p) {
    uint2 v;
    asm volatile("ld.global.nc.L1::no_allocate.v2.u32 {%0,%1}, [%2];" : "=r"(v.x), "=r"(v.y) : "l"(p));
    return v;
}
__device__ __forceinline__ unsigned long long pack_tagged(float v, uint32_t tag) {
    return ((unsigned long long)tag << 32) | __float_as_uint(v);
}
__device__ __forceinline__ void ld_tagged(const unsigned long long* p, float& v, uint32_t& t) {
    unsigned long long w;
    asm volatile("ld.relaxed.gpu.global.u64 %0, [%1];" : "=l"(w) : "l"(p) : "memory");
    v = __uint_as_float((uint32_t)w);
    t = (uint32_t)(w >> 32);
}
__device__ __forceinline__ float warp_sum(float v) {
#pragma unroll
    for (int o = 16; o > 0; o >>= 1) v += __shfl_xor_sync(0xffffffffu, v, o);
    return v;
}

__device__ __forceinline__ void fma8(float* acc, float s, const uint4& v) {
    acc[0] = fmaf(s, bflo(v.x), acc[0]);
    acc[1] = fmaf(s, bfhi(v.x), acc[1]);
    acc[2] = fmaf(s, bflo(v.y), acc[2]);
    acc[3] = fmaf(s, bfhi(v.y), acc[3]);
    acc[4] = fmaf(s, bflo(v.z), acc[4]);
    acc[5] = fmaf(s, bfhi(v.z), acc[5]);
    acc[6] = fmaf(s, bflo(v.w), acc[6]);
    acc[7] = fmaf(s, bfhi(v.w), acc[7]);
}
__device__ __forceinline__ float dot8(const float* q, const uint4& v) {
    float a = q[0] * bflo(v.x);
    float b = q[1] * bfhi(v.x);
    a = fmaf(q[2], bflo(v.y), a);
    b = fmaf(q[3], bfhi(v.y), b);
    a = fmaf(q[4], bflo(v.z), a);
    b = fmaf(q[5], bfhi(v.z), b);
    a = fmaf(q[6], bflo(v.w), a);
    b = fmaf(q[7], bfhi(v.w), b);
    return a + b;
}

__device__ __noinline__ void warp_layernorm(float* v) {
    float s = 0.f;
#pragma unroll
    for (int i = 0; i < 20; i++) s += v[i];
    s = warp_sum(s);
    const float mean = s * (1.0f / D_MODEL);
    float ss = 0.f;
#pragma unroll
    for (int i = 0; i < 20; i++) {
        float d = v[i] - mean;
        ss = fmaf(d, d, ss);
    }
    ss = warp_sum(ss);
    const float m_bf = bfr(mean);
    const float v_bf = bfr(ss * (1.0f / D_MODEL));
    const float den = bfr(sqrtf(bfr(v_bf + 1e-5f)));
#pragma unroll
    for (int i = 0; i < 20; i++) v[i] = bfr(__fdiv_rn(bfr(v[i] - m_bf), den));
}

constexpr float L2E = 1.4426950408889634f;

__device__ __forceinline__ void ml_merge(float& m, float& l, int o) {
    const float mo = __shfl_xor_sync(0xffffffffu, m, o);
    const float lo = __shfl_xor_sync(0xffffffffu, l, o);
    const float mn = fmaxf(m, mo);
    l = l * ex2((m - mn) * L2E) + lo * ex2((mo - mn) * L2E);
    m = mn;
}

__global__ void __launch_bounds__(NTHREADS, 1)
fused_decode_kernel(const __nv_bfloat16* __restrict__ x, const __nv_bfloat16* __restrict__ kc,
                    const __nv_bfloat16* __restrict__ vc, const __nv_bfloat16* __restrict__ wq,
                    const __nv_bfloat16* __restrict__ wo, const __nv_bfloat16* __restrict__ w1,
                    const __nv_bfloat16* __restrict__ b1, const __nv_bfloat16* __restrict__ w2,
                    const __nv_bfloat16* __restrict__ b2, __nv_bfloat16* __restrict__ out) {
    extern __shared__ __align__(1024) unsigned char smem[];
    const int tid = threadIdx.x, warp = tid >> 5, lane = tid & 31;
    const int cta = blockIdx.x, head = cta >> 2, split = cta & 3;
    Scratch* const g = &g_scr;

    float* sc = reinterpret_cast<float*>(smem + OFF_SC);
    float* xn_s = reinterpret_cast<float*>(smem + OFF_XN);
    float* q_s = reinterpret_cast<float*>(smem + OFF_Q);
    float* red = reinterpret_cast<float*>(smem + OFF_RED);
    float* misc = reinterpret_cast<float*>(smem + OFF_MISC);
    const uint32_t bar_full = s2u(smem + OFF_BAR);
    const uint32_t bar_empty = bar_full + STAGES * 8;
    const uint32_t bar_wo = bar_full + 2 * STAGES * 8;

    TL(0);
    if (warp == 8) {
        if (lane < 2 * STAGES + 1) mbar_init(bar_full + lane * 8, (lane >= STAGES && lane < 2 * STAGES) ? 8 : 1);
        asm volatile("fence.mbarrier_init.release.cluster;" ::: "memory");
    } else if (warp < 8) {
        const unsigned char* wqp = reinterpret_cast<const unsigned char*>(wq) + (size_t)(head * DH + split * WO_ROWS) * 2 +
                                   (tid & 3) * 16 + (size_t)(tid >> 2) * (NHEAD * DH * 2);
        uint32_t dst = s2u(smem + OFF_WO) + tid * 16;
#pragma unroll 1
        for (int i = 0; i < 10; i++) {
            asm volatile("cp.async.cg.shared.global [%0], [%1], 16;" ::"r"(dst), "l"(wqp) : "memory");
            dst += 4096;
            wqp += (size_t)64 * (NHEAD * DH * 2);
        }
        asm volatile("cp.async.commit_group;" ::: "memory");
    }
    __syncthreads();

    if (warp == 8) {
        if (lane == 0) {
            const unsigned char* kbase =
                reinterpret_cast<const unsigned char*>(kc) + (size_t)head * SK * (DH * 2) + (size_t)split * TILE_BYTES;
            const unsigned char* vbase =
                reinterpret_cast<const unsigned char*>(vc) + (size_t)head * SK * (DH * 2) + (size_t)split * TILE_BYTES;
            const uint32_t ring = s2u(smem + OFF_RING);
            int s = 0, sl = 0;
            uint32_t ph = 1, phl = 0;
            uint64_t pol;
            asm volatile("createpolicy.fractional.L2::evict_first.b64 %0, 1.0;" : "=l"(pol));
#pragma unroll 1
            for (int t = 0; t < 2 * NT; t++) {
                if (t >= INFLIGHT) {
                    mbar_wait(bar_full + sl * 8, phl);
                    if (++sl == STAGES) { sl = 0; phl ^= 1; }
                }
                mbar_wait(bar_empty + s * 8, ph);
                mbar_expect(bar_full + s * 8, TILE_BYTES);
                const unsigned char* src =
                    (t < NT) ? (kbase + (size_t)t * (NSPLIT * TILE_BYTES)) : (vbase + (size_t)(t - NT) * (NSPLIT * TILE_BYTES));
                bulk_g2s_hint(ring + s * TILE_BYTES, src, TILE_BYTES, bar_full + s * 8, pol);
                if (t == STAGES) {
                    mbar_expect(bar_wo, WO_BYTES);
                    bulk_g2s(s2u(smem + OFF_WO),
                             reinterpret_cast<const unsigned char*>(wo) + (size_t)(head * DH + split * WO_ROWS) * (D_MODEL * 2),
                             WO_BYTES, bar_wo);
                }
                if (++s == STAGES) { s = 0; ph ^= 1; }
            }
        }
    } else if (warp == 9) {
        unsigned int bbase;
        asm volatile("ld.relaxed.gpu.global.u32 %0, [%1];" : "=r"(bbase) : "l"(&g->cntB) : "memory");
        bbase &= ~(unsigned)(NCTA - 1);
        if (cta < MLP_CTAS) {
            const int f0 = cta * MLP_COLS;
            float* y_s = reinterpret_cast<float*>(smem + OFF_Y);
            {
                float v[20];
#pragma unroll
                for (int i = 0; i < 20; i++) v[i] = __bfloat162float(x[lane + 32 * i]);
                warp_layernorm(v);
                warp_layernorm(v);
#pragma unroll
                for (int i = 0; i < 20; i++) y_s[lane + 32 * i] = v[i];
            }
            __syncwarp();
            float acc[8];
#pragma unroll
            for (int i = 0; i < 8; i++) acc[i] = 0.f;
            const unsigned char* w1p =
                reinterpret_cast<const unsigned char*>(w1) + (size_t)f0 * 2 + (lane & 3) * 16 + (size_t)(lane >> 2) * (FF * 2);
#pragma unroll 1
            for (int b = 0; b < 8; b++) {
                uint4 wv[10];
#pragma unroll
                for (int i = 0; i < 10; i++) wv[i] = ldg_nc16(w1p + (size_t)((b * 10 + i) * 8) * (FF * 2));
#pragma unroll
                for (int i = 0; i < 10; i++) fma8(acc, y_s[(b * 10 + i) * 8 + (lane >> 2)], wv[i]);
            }
#pragma unroll
            for (int i = 0; i < 8; i++) {
#pragma unroll
                for (int o = 4; o <= 16; o <<= 1) acc[i] += __shfl_xor_sync(0xffffffffu, acc[i], o);
            }
            float hval[8];
#pragma unroll
            for (int i = 0; i < 8; i++) {
                const int f = f0 + (lane & 3) * 8 + i;
                const float pre = bfr(bfr(acc[i]) + __bfloat162float(b1[f]));
                const float inner = 0.7978845608028654f * (pre + 0.044715f * pre * pre * pre);
                hval[i] = bfr(0.5f * pre * (1.0f + tanhf(inner)));
            }
            float o[20];
#pragma unroll
            for (int i = 0; i < 20; i++) o[i] = 0.f;
            const unsigned char* w2p = reinterpret_cast<const unsigned char*>(w2) + (size_t)f0 * (D_MODEL * 2) + lane * 8;
#pragma unroll 1
            for (int rb = 0; rb < 4; rb++) {
                uint2 wv[8][5];
#pragma unroll
                for (int r = 0; r < 8; r++)
#pragma unroll
                    for (int i = 0; i < 5; i++) wv[r][i] = ldg_nc8(w2p + (size_t)(rb * 8 + r) * (D_MODEL * 2) + i * 256);
#pragma unroll
                for (int r = 0; r < 8; r++) {
                    const float hv = __shfl_sync(0xffffffffu, hval[r], rb);
#pragma unroll
                    for (int i = 0; i < 5; i++) {
                        o[i * 4 + 0] = fmaf(hv, bflo(wv[r][i].x), o[i * 4 + 0]);
                        o[i * 4 + 1] = fmaf(hv, bfhi(wv[r][i].x), o[i * 4 + 1]);
                        o[i * 4 + 2] = fmaf(hv, bflo(wv[r][i].y), o[i * 4 + 2]);
                        o[i * 4 + 3] = fmaf(hv, bfhi(wv[r][i].y), o[i * 4 + 3]);
                    }
                }
            }
#pragma unroll
            for (int i = 0; i < 5; i++)
#pragma unroll
                for (int j = 0; j < 4; j++) atomicAdd(&g->accB[(lane + 32 * i) * 4 + j], o[i * 4 + j]);
            __threadfence();
            __syncwarp();
        }
        if (lane == 0) atomicAdd(&g->cntB, 1u);
        mbar_wait(bar_empty + (STAGES - 1) * 8, 0);
        mbar_wait(bar_empty + (STAGES - 1) * 8, 1);
        if (lane < OUT_COLS) {
            unsigned int c;
            int it = 0;
            while (true) {
                asm volatile("ld.acquire.gpu.global.u32 %0, [%1];" : "=r"(c) : "l"(&g->cntB) : "memory");
                if (c - bbase >= (unsigned)NCTA) break;
                __nanosleep(1000);
                if (++it > (1 << 22)) __trap();
            }
            float* ap = &g->accB[cta * OUT_COLS + lane];
            const float b = __ldcg(ap);
            __stcg(ap, 0.f);
            misc[40 + lane] = bfr(bfr(b) + __bfloat162float(b2[cta * OUT_COLS + lane]));
        }
        __syncwarp();
        asm volatile("bar.arrive 3, 288;" ::: "memory");
    } else {
        if (tid == 0) {
            unsigned int a;
            asm volatile("ld.relaxed.gpu.global.u32 %0, [%1];" : "=r"(a) : "l"(&g->arrive) : "memory");
            misc[63] = __uint_as_float(a & ~(unsigned)(NCTA - 1));
        }
        float xcol = 0.f;
        if (lane == 0 && warp < OUT_COLS) xcol = __bfloat162float(x[cta * OUT_COLS + warp]);
        float xv[3];
#pragma unroll
        for (int j = 0; j < 3; j++) xv[j] = (tid + 256 * j < D_MODEL) ? __bfloat162float(x[tid + 256 * j]) : 0.f;
        {
            float s = warp_sum(xv[0] + xv[1] + xv[2]);
            if (lane == 0) misc[warp] = s;
            cbar();
            float tot = 0.f;
#pragma unroll
            for (int w = 0; w < 8; w++) tot += misc[w];
            const float mean = tot * (1.0f / D_MODEL);
            float ss = 0.f;
#pragma unroll
            for (int j = 0; j < 3; j++) {
                const float d = (tid + 256 * j < D_MODEL) ? xv[j] - mean : 0.f;
                ss = fmaf(d, d, ss);
            }
            ss = warp_sum(ss);
            if (lane == 0) misc[8 + warp] = ss;
            cbar();
            float tss = 0.f;
#pragma unroll
            for (int w = 0; w < 8; w++) tss += misc[8 + w];
            const float m_bf = bfr(mean);
            const float v_bf = bfr(tss * (1.0f / D_MODEL));
            const float den = bfr(__fsqrt_rn(bfr(v_bf + 1e-5f)));
#pragma unroll 1
            for (int j = 0; j < 3; j++) {
                const float xj = j == 0 ? xv[0] : (j == 1 ? xv[1] : xv[2]);
                if (tid + 256 * j < D_MODEL) xn_s[tid + 256 * j] = bfr(__fdiv_rn(bfr(xj - m_bf), den));
            }
        }
        const unsigned int arrive_base = __float_as_uint(misc[63]);
        const uint32_t tag = (arrive_base >> 7) % 65535u + 1u;
        asm volatile("cp.async.wait_all;" ::: "memory");
        cbar();
        TL(8);
        {
            float qa[8];
#pragma unroll
            for (int i = 0; i < 8; i++) qa[i] = 0.f;
            const unsigned char* wp = smem + OFF_WO + tid * 16;
#pragma unroll 2
            for (int i = 0; i < 10; i++)
                fma8(qa, xn_s[i * 64 + (tid >> 2)], *reinterpret_cast<const uint4*>(wp + i * 4096));
#pragma unroll
            for (int i = 0; i < 8; i++) {
                qa[i] += __shfl_xor_sync(0xffffffffu, qa[i], 4);
                qa[i] += __shfl_xor_sync(0xffffffffu, qa[i], 8);
                qa[i] += __shfl_xor_sync(0xffffffffu, qa[i], 16);
            }
            if (lane < 4) {
                *reinterpret_cast<float4*>(&red[warp * 32 + lane * 8]) = make_float4(qa[0], qa[1], qa[2], qa[3]);
                *reinterpret_cast<float4*>(&red[warp * 32 + lane * 8 + 4]) = make_float4(qa[4], qa[5], qa[6], qa[7]);
            }
        }
        cbar();
        if (warp == 0) {
            float s = 0.f;
#pragma unroll
            for (int w = 0; w < 8; w++) s += red[w * 32 + lane];
            const uint32_t wrd = (__float_as_uint(bfr(s)) & 0xffff0000u) | tag;
            asm volatile("st.relaxed.gpu.global.u32 [%0], %1;" ::"l"(&g->q[cta * WO_ROWS + lane]), "r"(wrd) : "memory");
            uint32_t w0, w1_, w2_, w3;
            int it = 0;
            while (true) {
                asm volatile("ld.relaxed.gpu.global.v4.u32 {%0,%1,%2,%3}, [%4];"
                             : "=r"(w0), "=r"(w1_), "=r"(w2_), "=r"(w3)
                             : "l"(&g->q[head * DH + lane * 4])
                             : "memory");
                if ((((w0 ^ tag) | (w1_ ^ tag) | (w2_ ^ tag) | (w3 ^ tag)) & 0xffffu) == 0u) break;
                __nanosleep(40);
                if (++it > (1 << 22)) __trap();
            }
            *reinterpret_cast<uint4*>(&q_s[lane * 4]) =
                make_uint4(w0 & 0xffff0000u, w1_ & 0xffff0000u, w2_ & 0xffff0000u, w3 & 0xffff0000u);
        }
        cbar();
        float q[8];
        {
            const float4 qa = *reinterpret_cast<const float4*>(&q_s[(lane & 15) * 8]);
            const float4 qb = *reinterpret_cast<const float4*>(&q_s[(lane & 15) * 8 + 4]);
            q[0] = qa.x; q[1] = qa.y; q[2] = qa.z; q[3] = qa.w;
            q[4] = qb.x; q[5] = qb.y; q[6] = qb.z; q[7] = qb.w;
        }

        TL(1);
        const float scale = 0.08838834764831845f;
        const unsigned char* ring = smem + OFF_RING;
        int s = 0;
        uint32_t ph = 0;
        float mrun = -INFINITY, lrun = 0.f;
        const int lane_off = (warp * 8 + (lane >> 4)) * (DH * 2) + (lane & 15) * 16;
        const bool l3 = lane & 8, l2 = lane & 4;
        const int key_off = warp * 8 + 2 * ((l3 ? 2 : 0) + (l2 ? 1 : 0)) + (lane >> 4);
#pragma unroll 1
        for (int t = 0; t < NT; t++) {
            mbar_wait(bar_full + s * 8, ph);
            const unsigned char* tp = ring + s * TILE_BYTES + lane_off;
            uint4 kv[4];
#pragma unroll
            for (int j = 0; j < 4; j++) kv[j] = *reinterpret_cast<const uint4*>(tp + j * 2 * (DH * 2));
            float a0 = dot8(q, kv[0]), a1 = dot8(q, kv[1]), a2 = dot8(q, kv[2]), a3 = dot8(q, kv[3]);
            __syncwarp();
            if (lane == 0) mbar_arrive(bar_empty + s * 8);
            float s0 = l3 ? a0 : a2, s1 = l3 ? a1 : a3;
            float k0 = l3 ? a2 : a0, k1 = l3 ? a3 : a1;
            k0 += __shfl_xor_sync(0xffffffffu, s0, 8);
            k1 += __shfl_xor_sync(0xffffffffu, s1, 8);
            float sn = l2 ? k0 : k1, kp = l2 ? k1 : k0;
            kp += __shfl_xor_sync(0xffffffffu, sn, 4);
            kp += __shfl_xor_sync(0xffffffffu, kp, 2);
            kp += __shfl_xor_sync(0xffffffffu, kp, 1);
            const float sv = bfr(bfr(kp) * scale);
            const float mnew = fmaxf(mrun, sv);
            lrun = lrun * ex2((mrun - mnew) * L2E) + ex2((sv - mnew) * L2E);
            mrun = mnew;
            if ((lane & 3) == 0) sc[t * TILE + key_off] = sv;
            if (++s == STAGES) { s = 0; ph ^= 1; }
        }

        TL(2);
        {
            if (lane & 3) lrun = 0.f;
#pragma unroll 1
            for (int o = 16; o > 0; o >>= 1) ml_merge(mrun, lrun, o);
            if (lane == 0) { misc[16 + warp] = mrun; misc[24 + warp] = lrun; }
            cbar();
            if (warp == 0) {
                float m = (lane < 8) ? misc[16 + lane] : -INFINITY;
                float l = (lane < 8) ? misc[24 + lane] : 0.f;
#pragma unroll 1
                for (int o = 4; o > 0; o >>= 1) ml_merge(m, l, o);
                if (lane == 0) {
                    unsigned long long pk =
                        ((unsigned long long)__float_as_uint(l) << 32) | (__float_as_uint(m) & 0xffff0000u) | tag;
                    asm volatile("st.relaxed.gpu.global.u64 [%0], %1;" ::"l"(&g->ml[cta]), "l"(pk) : "memory");
                }
                m = -INFINITY;
                l = 0.f;
                if (lane < NSPLIT) {
                    unsigned long long pk;
                    int it = 0;
                    do {
                        asm volatile("ld.relaxed.gpu.global.u64 %0, [%1];" : "=l"(pk) : "l"(&g->ml[(cta & ~3) + lane]) : "memory");
                        if (++it > (1 << 24)) __trap();
                    } while (((uint32_t)pk & 0xffffu) != tag);
                    m = __uint_as_float((uint32_t)pk & 0xffff0000u);
                    l = __uint_as_float((uint32_t)(pk >> 32));
                }
#pragma unroll 1
                for (int o = 2; o > 0; o >>= 1) ml_merge(m, l, o);
                if (lane == 0) { misc[32] = m; misc[33] = __fdiv_rn(1.0f, l); }
            }
            cbar();
        }
        const float mg = misc[32], inv_l = misc[33];

        TL(3);
        float oa[8];
#pragma unroll
        for (int i = 0; i < 8; i++) oa[i] = 0.f;
        const int pkey = warp * 8 + (lane >> 4);
#pragma unroll 1
        for (int t = 0; t < NT; t++) {
            float p[4];
#pragma unroll
            for (int j = 0; j < 4; j++) p[j] = bfr(ex2((sc[t * TILE + pkey + 2 * j] - mg) * L2E) * inv_l);
            mbar_wait(bar_full + s * 8, ph);
            const unsigned char* tp = ring + s * TILE_BYTES + lane_off;
            uint4 vv[4];
#pragma unroll
            for (int j = 0; j < 4; j++) vv[j] = *reinterpret_cast<const uint4*>(tp + j * 2 * (DH * 2));
#pragma unroll
            for (int j = 0; j < 4; j++) fma8(oa, p[j], vv[j]);
            __syncwarp();
            if (lane == 0) mbar_arrive(bar_empty + s * 8);
            if (++s == STAGES) { s = 0; ph ^= 1; }
        }
        TL(4);

#pragma unroll
        for (int i = 0; i < 8; i++) oa[i] += __shfl_xor_sync(0xffffffffu, oa[i], 16);
        if (lane < 16) {
            *reinterpret_cast<float4*>(&red[warp * DH + lane * 8]) = make_float4(oa[0], oa[1], oa[2], oa[3]);
            *reinterpret_cast<float4*>(&red[warp * DH + lane * 8 + 4]) = make_float4(oa[4], oa[5], oa[6], oa[7]);
        }
        cbar();
        if (tid < DH) {
            float v = 0.f;
#pragma unroll
            for (int w = 0; w < 8; w++) v += red[w * DH + tid];
            asm volatile("st.relaxed.gpu.global.u64 [%0], %1;" ::"l"(&g->op[cta * DH + tid]), "l"(pack_tagged(v, tag)) : "memory");
        }
        if (warp == 0) {
            const unsigned long long* opw = &g->op[(cta & ~3) * DH + split * WO_ROWS + lane];
            float v[NSPLIT];
            int it = 0;
            while (true) {
                uint32_t bad = 0u;
#pragma unroll
                for (int j = 0; j < NSPLIT; j++) {
                    uint32_t t;
                    ld_tagged(opw + j * DH, v[j], t);
                    bad |= t ^ tag;
                }
                if (!bad) break;
                __nanosleep(100);
                if (++it > (1 << 22)) __trap();
            }
            q_s[lane] = bfr((v[0] + v[1]) + (v[2] + v[3]));
        }
        mbar_wait(bar_wo, 0);
        cbar();
        TL(5);
        if (tid < 160) {
            float a0 = 0.f, a1 = 0.f, a2 = 0.f, a3 = 0.f;
            const unsigned char* wp = smem + OFF_WO + tid * 8;
#pragma unroll 1
            for (int r4 = 0; r4 < WO_ROWS / 4; r4++) {
                const float4 ov = *reinterpret_cast<const float4*>(&q_s[r4 * 4]);
                const float ovv[4] = {ov.x, ov.y, ov.z, ov.w};
#pragma unroll
                for (int k = 0; k < 4; k++) {
                    const uint2 w = *reinterpret_cast<const uint2*>(wp + (r4 * 4 + k) * (D_MODEL * 2));
                    a0 = fmaf(ovv[k], bflo(w.x), a0);
                    a1 = fmaf(ovv[k], bfhi(w.x), a1);
                    a2 = fmaf(ovv[k], bflo(w.y), a2);
                    a3 = fmaf(ovv[k], bfhi(w.y), a3);
                }
            }
            unsigned long long* dst = &g->outA[cta * D_MODEL + tid * 4];
            asm volatile("st.relaxed.gpu.global.v2.u64 [%0], {%1, %2};" ::"l"(dst), "l"(pack_tagged(a0, tag)), "l"(pack_tagged(a1, tag))
                         : "memory");
            asm volatile("st.relaxed.gpu.global.v2.u64 [%0], {%1, %2};" ::"l"(dst + 2), "l"(pack_tagged(a2, tag)),
                         "l"(pack_tagged(a3, tag))
                         : "memory");
        }
        if (tid == 255) asm volatile("red.relaxed.gpu.global.add.u32 [%0], %1;" ::"l"(&g->arrive), "r"(1u) : "memory");
        TL(6);
        {
            const unsigned long long* src = &g->outA[(tid & (NCTA - 1)) * D_MODEL + cta * OUT_COLS];
            uint32_t ok = tid < NCTA ? 0u : 1u;
            int it = 0;
            while (true) {
                if (!ok) {
                    uint32_t bad = 0u;
#pragma unroll
                    for (int k = 0; k < OUT_COLS; k++) {
                        float v;
                        uint32_t t;
                        ld_tagged(src + k, v, t);
                        red[k * NCTA + tid] = v;
                        bad |= t ^ tag;
                    }
                    ok = bad == 0u;
                }
                uint32_t all;
                asm volatile(
                    "{\n.reg .pred p, q;\nsetp.ne.u32 p, %1, 0;\nbar.red.and.pred q, 1, 256, p;\nselp.u32 %0, 1, 0, q;\n}"
                    : "=r"(all)
                    : "r"(ok)
                    : "memory");
                if (all) break;
                if (tid == 0) {
                    unsigned int cnt;
                    int it2 = 0;
                    while (true) {
                        asm volatile("ld.relaxed.gpu.global.u32 %0, [%1];" : "=r"(cnt) : "l"(&g->arrive) : "memory");
                        if (cnt - arrive_base >= (unsigned)(NCTA - GATE_SLACK)) break;
                        __nanosleep(100);
                        if (++it2 > (1 << 22)) __trap();
                    }
                }
                cbar();
                if (++it > (1 << 22)) __trap();
            }
        }
        TL(10);
        asm volatile("bar.sync 3, 288;" ::: "memory");
        if (warp < OUT_COLS) {
            const float* rp = red + warp * NCTA + lane;
            const float a = bfr(warp_sum((rp[0] + rp[32]) + (rp[64] + rp[96])));
            if (lane == 0) out[cta * OUT_COLS + warp] = __float2bfloat16_rn(bfr(xcol + a) + misc[40 + warp]);
        }
        TL(7);
    }
}

}

extern "C" void kernel_launch(void* const* d_in, const int* in_sizes, int n_in, void* d_out, int out_size) {
    const __nv_bfloat16* x = (const __nv_bfloat16*)d_in[0];
    const __nv_bfloat16* kc = (const __nv_bfloat16*)d_in[1];
    const __nv_bfloat16* vc = (const __nv_bfloat16*)d_in[2];
    const __nv_bfloat16* wq = (const __nv_bfloat16*)d_in[3];
    const __nv_bfloat16* wo = (const __nv_bfloat16*)d_in[4];
    const __nv_bfloat16* w1 = (const __nv_bfloat16*)d_in[6];
    const __nv_bfloat16* b1 = (const __nv_bfloat16*)d_in[7];
    const __nv_bfloat16* w2 = (const __nv_bfloat16*)d_in[8];
    const __nv_bfloat16* b2 = (const __nv_bfloat16*)d_in[9];
    static bool attr_set = false;
    if (!attr_set) {
        cudaFuncSetAttribute(fused_decode_kernel, cudaFuncAttributeMaxDynamicSharedMemorySize, SMEM_BYTES);
        attr_set = true;
    }
    fused_decode_kernel<<<NCTA, NTHREADS, SMEM_BYTES>>>(x, kc, vc, wq, wo, w1, b1, w2, b2, (__nv_bfloat16*)d_out);
}
```

```cpp
#include <cuda_runtime.h>
#include <cuda_bf16.h>
#include <stdint.h>

namespace {

constexpr int D_MODEL = 640;
constexpr int NHEAD = 32;
constexpr int SK = 16384;
constexpr int DH = 128;
constexpr int FF = 1728;
constexpr int NSPLIT = 4;
constexpr int NCTA = NHEAD * NSPLIT;
constexpr int KEYS_PER_CTA = SK / NSPLIT;
constexpr int TILE = 64;
constexpr int TILE_BYTES = TILE * DH * 2;
constexpr int NT = KEYS_PER_CTA / TILE;
constexpr int STAGES = 10;
#define INFLIGHT_N 4
constexpr int INFLIGHT = INFLIGHT_N;
constexpr int WO_ROWS = DH / NSPLIT;
constexpr int WO_BYTES = WO_ROWS * D_MODEL * 2;
constexpr int MLP_COLS = 32;
constexpr int MLP_CTAS = FF / MLP_COLS;
constexpr int OUT_COLS = D_MODEL / NCTA;
constexpr int NTHREADS = 320;
#define GATE_SLACK 4

constexpr int OFF_RING = 0;
constexpr int OFF_WO = OFF_RING + STAGES * TILE_BYTES;
constexpr int OFF_SC = OFF_WO + WO_BYTES;
constexpr int OFF_XN = OFF_SC + KEYS_PER_CTA * 4;
constexpr int OFF_Y = OFF_XN + D_MODEL * 4;
constexpr int OFF_RED = OFF_Y + D_MODEL * 4;
constexpr int OFF_Q = OFF_RED + 8 * DH * 4;
constexpr int OFF_MISC = OFF_Q + DH * 4;
constexpr int OFF_BAR = OFF_MISC + 256;
constexpr int SMEM_BYTES = OFF_BAR + (2 * STAGES + 1) * 8;

struct alignas(256) Scratch {
    uint32_t q[NHEAD * DH];
    unsigned long long ml[NCTA];
    unsigned long long op[NCTA * DH];
    unsigned long long outA[NCTA * D_MODEL];
    float accB[D_MODEL];
    unsigned int cntB;
    unsigned int arrive;
};
__device__ Scratch g_scr;

#define TL(i) do { } while (0)

__device__ __forceinline__ uint32_t s2u(const void* p) { return (uint32_t)__cvta_generic_to_shared(p); }
__device__ __forceinline__ void mbar_init(uint32_t a, uint32_t c) {
    asm volatile("mbarrier.init.shared::cta.b64 [%0], %1;" ::"r"(a), "r"(c));
}
__device__ __forceinline__ void mbar_expect(uint32_t a, uint32_t b) {
    asm volatile("mbarrier.arrive.expect_tx.shared::cta.b64 _, [%0], %1;" ::"r"(a), "r"(b) : "memory");
}
__device__ __forceinline__ void mbar_arrive(uint32_t a) {
    asm volatile("mbarrier.arrive.shared::cta.b64 _, [%0];" ::"r"(a) : "memory");
}
__device__ __forceinline__ void mbar_wait(uint32_t a, uint32_t ph) {
    uint32_t ok;
    int it = 0;
    do {
        asm volatile(
            "{\n.reg .pred p;\nmbarrier.try_wait.parity.shared::cta.b64 p, [%1], %2;\nselp.u32 %0,1,0,p;\n}"
            : "=r"(ok)
            : "r"(a), "r"(ph)
            : "memory");
        if (++it > (1 << 22)) __trap();
    } while (!ok);
}
__device__ __forceinline__ void bulk_g2s(uint32_t dst, const void* src, uint32_t bytes, uint32_t bar) {
    asm volatile("cp.async.bulk.shared::cluster.global.mbarrier::complete_tx::bytes [%0], [%1], %2, [%3];" ::"r"(dst),
                 "l"(src), "r"(bytes), "r"(bar)
                 : "memory");
}
__device__ __forceinline__ void bulk_g2s_hint(uint32_t dst, const void* src, uint32_t bytes, uint32_t bar, uint64_t pol) {
    asm volatile("cp.async.bulk.shared::cluster.global.mbarrier::complete_tx::bytes.L2::cache_hint [%0], [%1], %2, [%3], %4;" ::"r"(dst),
                 "l"(src), "r"(bytes), "r"(bar), "l"(pol)
                 : "memory");
}
__device__ __forceinline__ void cbar() { asm volatile("bar.sync 1, 256;" ::: "memory"); }

__device__ __forceinline__ float bfr(float x) { return __bfloat162float(__float2bfloat16_rn(x)); }
__device__ __forceinline__ float bflo(uint32_t u) { return __uint_as_float(u << 16); }
__device__ __forceinline__ float bfhi(uint32_t u) { return __uint_as_float(u & 0xffff0000u); }
__device__ __forceinline__ float ex2(float x) {
    float r;
    asm("ex2.approx.ftz.f32 %0, %1;" : "=f"(r) : "f"(x));
    return r;
}

__device__ __forceinline__ uint4 ldg_nc16(const void* p) {
    uint4 v;
    asm volatile("ld.global.nc.L1::no_allocate.v4.u32 {%0,%1,%2,%3}, [%4];"
                 : "=r"(v.x), "=r"(v.y), "=r"(v.z), "=r"(v.w)
                 : "l"(p));
    return v;
}
__device__ __forceinline__ uint2 ldg_nc8(const void* p) {
    uint2 v;
    asm volatile("ld.global.nc.L1::no_allocate.v2.u32 {%0,%1}, [%2];" : "=r"(v.x), "=r"(v.y) : "l"(p));
    return v;
}
__device__ __forceinline__ unsigned long long pack_tagged(float v, uint32_t tag) {
    return ((unsigned long long)tag << 32) | __float_as_uint(v);
}
__device__ __forceinline__ void ld_tagged(const unsigned long long* p, float& v, uint32_t& t) {
    unsigned long long w;
    asm volatile("ld.relaxed.gpu.global.u64 %0, [%1];" : "=l"(w) : "l"(p) : "memory");
    v = __uint_as_float((uint32_t)w);
    t = (uint32_t)(w >> 32);
}
__device__ __forceinline__ float warp_sum(float v) {
#pragma unroll
    for (int o = 16; o > 0; o >>= 1) v += __shfl_xor_sync(0xffffffffu, v, o);
    return v;
}

__device__ __forceinline__ void fma8(float* acc, float s, const uint4& v) {
    acc[0] = fmaf(s, bflo(v.x), acc[0]);
    acc[1] = fmaf(s, bfhi(v.x), acc[1]);
    acc[2] = fmaf(s, bflo(v.y), acc[2]);
    acc[3] = fmaf(s, bfhi(v.y), acc[3]);
    acc[4] = fmaf(s, bflo(v.z), acc[4]);
    acc[5] = fmaf(s, bfhi(v.z), acc[5]);
    acc[6] = fmaf(s, bflo(v.w), acc[6]);
    acc[7] = fmaf(s, bfhi(v.w), acc[7]);
}
__device__ __forceinline__ float dot8(const float* q, const uint4& v) {
    float a = q[0] * bflo(v.x);
    float b = q[1] * bfhi(v.x);
    a = fmaf(q[2], bflo(v.y), a);
    b = fmaf(q[3], bfhi(v.y), b);
    a = fmaf(q[4], bflo(v.z), a);
    b = fmaf(q[5], bfhi(v.z), b);
    a = fmaf(q[6], bflo(v.w), a);
    b = fmaf(q[7], bfhi(v.w), b);
    return a + b;
}

__device__ __noinline__ void warp_layernorm(float* v) {
    float s = 0.f;
#pragma unroll
    for (int i = 0; i < 20; i++) s += v[i];
    s = warp_sum(s);
    const float mean = s * (1.0f / D_MODEL);
    float ss = 0.f;
#pragma unroll
    for (int i = 0; i < 20; i++) {
        float d = v[i] - mean;
        ss = fmaf(d, d, ss);
    }
    ss = warp_sum(ss);
    const float m_bf = bfr(mean);
    const float v_bf = bfr(ss * (1.0f / D_MODEL));
    const float den = bfr(sqrtf(bfr(v_bf + 1e-5f)));
#pragma unroll
    for (int i = 0; i < 20; i++) v[i] = bfr(__fdiv_rn(bfr(v[i] - m_bf), den));
}

constexpr float L2E = 1.4426950408889634f;

__device__ __forceinline__ void ml_merge(float& m, float& l, int o) {
    const float mo = __shfl_xor_sync(0xffffffffu, m, o);
    const float lo = __shfl_xor_sync(0xffffffffu, l, o);
    const float mn = fmaxf(m, mo);
    l = l * ex2((m - mn) * L2E) + lo * ex2((mo - mn) * L2E);
    m = mn;
}

__global__ void __launch_bounds__(NTHREADS, 1)
fused_decode_kernel(const __nv_bfloat16* __restrict__ x, const __nv_bfloat16* __restrict__ kc,
                    const __nv_bfloat16* __restrict__ vc, const __nv_bfloat16* __restrict__ wq,
                    const __nv_bfloat16* __restrict__ wo, const __nv_bfloat16* __restrict__ w1,
                    const __nv_bfloat16* __restrict__ b1, const __nv_bfloat16* __restrict__ w2,
                    const __nv_bfloat16* __restrict__ b2, __nv_bfloat16* __restrict__ out) {
    extern __shared__ __align__(1024) unsigned char smem[];
    const int tid = threadIdx.x, warp = tid >> 5, lane = tid & 31;
    const int cta = blockIdx.x, head = cta >> 2, split = cta & 3;
    Scratch* const g = &g_scr;

    float* sc = reinterpret_cast<float*>(smem + OFF_SC);
    float* xn_s = reinterpret_cast<float*>(smem + OFF_XN);
    float* q_s = reinterpret_cast<float*>(smem + OFF_Q);
    float* red = reinterpret_cast<float*>(smem + OFF_RED);
    float* misc = reinterpret_cast<float*>(smem + OFF_MISC);
    const uint32_t bar_full = s2u(smem + OFF_BAR);
    const uint32_t bar_empty = bar_full + STAGES * 8;
    const uint32_t bar_wo = bar_full + 2 * STAGES * 8;

    TL(0);
    if (warp == 8) {
        if (lane < 2 * STAGES + 1) mbar_init(bar_full + lane * 8, (lane >= STAGES && lane < 2 * STAGES) ? 8 : 1);
        asm volatile("fence.mbarrier_init.release.cluster;" ::: "memory");
        __syncwarp();
        if (lane == 0) {
            uint64_t pol;
            asm volatile("createpolicy.fractional.L2::evict_first.b64 %0, 1.0;" : "=l"(pol));
            const unsigned char* kb =
                reinterpret_cast<const unsigned char*>(kc) + (size_t)head * SK * (DH * 2) + (size_t)split * TILE_BYTES;
#pragma unroll 1
            for (int t = 0; t < INFLIGHT; t++) {
                mbar_expect(bar_full + t * 8, TILE_BYTES);
                bulk_g2s_hint(s2u(smem + OFF_RING) + t * TILE_BYTES, kb + (size_t)t * (NSPLIT * TILE_BYTES), TILE_BYTES,
                              bar_full + t * 8, pol);
            }
        }
    } else if (warp < 8) {
        const unsigned char* wqp = reinterpret_cast<const unsigned char*>(wq) + (size_t)(head * DH + split * WO_ROWS) * 2 +
                                   (tid & 3) * 16 + (size_t)(tid >> 2) * (NHEAD * DH * 2);
        uint32_t dst = s2u(smem + OFF_WO) + tid * 16;
#pragma unroll 1
        for (int i = 0; i < 10; i++) {
            asm volatile("cp.async.cg.shared.global [%0], [%1], 16;" ::"r"(dst), "l"(wqp) : "memory");
            dst += 4096;
            wqp += (size_t)64 * (NHEAD * DH * 2);
        }
        asm volatile("cp.async.commit_group;" ::: "memory");
    }
    __syncthreads();

    if (warp == 8) {
        if (lane == 0) {
            const unsigned char* kbase =
                reinterpret_cast<const unsigned char*>(kc) + (size_t)head * SK * (DH * 2) + (size_t)split * TILE_BYTES;
            const unsigned char* vbase =
                reinterpret_cast<const unsigned char*>(vc) + (size_t)head * SK * (DH * 2) + (size_t)split * TILE_BYTES;
            const uint32_t ring = s2u(smem + OFF_RING);
            int s = INFLIGHT, sl = 0;
            uint32_t ph = 1, phl = 0;
            uint64_t pol;
            asm volatile("createpolicy.fractional.L2::evict_first.b64 %0, 1.0;" : "=l"(pol));
#pragma unroll 1
            for (int t = INFLIGHT; t < 2 * NT; t++) {
                mbar_wait(bar_full + sl * 8, phl);
                if (++sl == STAGES) { sl = 0; phl ^= 1; }
                mbar_wait(bar_empty + s * 8, ph);
                mbar_expect(bar_full + s * 8, TILE_BYTES);
                const unsigned char* src =
                    (t < NT) ? (kbase + (size_t)t * (NSPLIT * TILE_BYTES)) : (vbase + (size_t)(t - NT) * (NSPLIT * TILE_BYTES));
                bulk_g2s_hint(ring + s * TILE_BYTES, src, TILE_BYTES, bar_full + s * 8, pol);
                if (t == STAGES) {
                    mbar_expect(bar_wo, WO_BYTES);
                    bulk_g2s(s2u(smem + OFF_WO),
                             reinterpret_cast<const unsigned char*>(wo) + (size_t)(head * DH + split * WO_ROWS) * (D_MODEL * 2),
                             WO_BYTES, bar_wo);
                }
                if (++s == STAGES) { s = 0; ph ^= 1; }
            }
        }
    } else if (warp == 9) {
        unsigned int bbase;
        asm volatile("ld.relaxed.gpu.global.u32 %0, [%1];" : "=r"(bbase) : "l"(&g->cntB) : "memory");
        bbase &= ~(unsigned)(NCTA - 1);
        if (cta < MLP_CTAS) {
            const int f0 = cta * MLP_COLS;
            float* y_s = reinterpret_cast<float*>(smem + OFF_Y);
            {
                float v[20];
#pragma unroll
                for (int i = 0; i < 20; i++) v[i] = __bfloat162float(x[lane + 32 * i]);
                warp_layernorm(v);
                warp_layernorm(v);
#pragma unroll
                for (int i = 0; i < 20; i++) y_s[lane + 32 * i] = v[i];
            }
            __syncwarp();
            float acc[8];
#pragma unroll
            for (int i = 0; i < 8; i++) acc[i] = 0.f;
            const unsigned char* w1p =
                reinterpret_cast<const unsigned char*>(w1) + (size_t)f0 * 2 + (lane & 3) * 16 + (size_t)(lane >> 2) * (FF * 2);
#pragma unroll 1
            for (int b = 0; b < 8; b++) {
                uint4 wv[10];
#pragma unroll
                for (int i = 0; i < 10; i++) wv[i] = ldg_nc16(w1p + (size_t)((b * 10 + i) * 8) * (FF * 2));
#pragma unroll
                for (int i = 0; i < 10; i++) fma8(acc, y_s[(b * 10 + i) * 8 + (lane >> 2)], wv[i]);
            }
#pragma unroll
            for (int i = 0; i < 8; i++) {
#pragma unroll
                for (int o = 4; o <= 16; o <<= 1) acc[i] += __shfl_xor_sync(0xffffffffu, acc[i], o);
            }
            float hval[8];
#pragma unroll
            for (int i = 0; i < 8; i++) {
                const int f = f0 + (lane & 3) * 8 + i;
                const float pre = bfr(bfr(acc[i]) + __bfloat162float(b1[f]));
                const float inner = 0.7978845608028654f * (pre + 0.044715f * pre * pre * pre);
                hval[i] = bfr(0.5f * pre * (1.0f + tanhf(inner)));
            }
            float o[20];
#pragma unroll
            for (int i = 0; i < 20; i++) o[i] = 0.f;
            const unsigned char* w2p = reinterpret_cast<const unsigned char*>(w2) + (size_t)f0 * (D_MODEL * 2) + lane * 8;
#pragma unroll 1
            for (int rb = 0; rb < 4; rb++) {
                uint2 wv[8][5];
#pragma unroll
                for (int r = 0; r < 8; r++)
#pragma unroll
                    for (int i = 0; i < 5; i++) wv[r][i] = ldg_nc8(w2p + (size_t)(rb * 8 + r) * (D_MODEL * 2) + i * 256);
#pragma unroll
                for (int r = 0; r < 8; r++) {
                    const float hv = __shfl_sync(0xffffffffu, hval[r], rb);
#pragma unroll
                    for (int i = 0; i < 5; i++) {
                        o[i * 4 + 0] = fmaf(hv, bflo(wv[r][i].x), o[i * 4 + 0]);
                        o[i * 4 + 1] = fmaf(hv, bfhi(wv[r][i].x), o[i * 4 + 1]);
                        o[i * 4 + 2] = fmaf(hv, bflo(wv[r][i].y), o[i * 4 + 2]);
                        o[i * 4 + 3] = fmaf(hv, bfhi(wv[r][i].y), o[i * 4 + 3]);
                    }
                }
            }
#pragma unroll
            for (int i = 0; i < 5; i++)
#pragma unroll
                for (int j = 0; j < 4; j++) atomicAdd(&g->accB[(lane + 32 * i) * 4 + j], o[i * 4 + j]);
            __threadfence();
            __syncwarp();
        }
        if (lane == 0) atomicAdd(&g->cntB, 1u);
        mbar_wait(bar_empty + (STAGES - 1) * 8, 0);
        mbar_wait(bar_empty + (STAGES - 1) * 8, 1);
        if (lane < OUT_COLS) {
            unsigned int c;
            int it = 0;
            while (true) {
                asm volatile("ld.acquire.gpu.global.u32 %0, [%1];" : "=r"(c) : "l"(&g->cntB) : "memory");
                if (c - bbase >= (unsigned)NCTA) break;
                __nanosleep(1000);
                if (++it > (1 << 22)) __trap();
            }
            float* ap = &g->accB[cta * OUT_COLS + lane];
            const float b = __ldcg(ap);
            __stcg(ap, 0.f);
            misc[40 + lane] = bfr(bfr(b) + __bfloat162float(b2[cta * OUT_COLS + lane]));
        }
        __syncwarp();
        asm volatile("bar.arrive 3, 288;" ::: "memory");
    } else {
        if (tid == 0) {
            unsigned int a;
            asm volatile("ld.relaxed.gpu.global.u32 %0, [%1];" : "=r"(a) : "l"(&g->arrive) : "memory");
            misc[63] = __uint_as_float(a & ~(unsigned)(NCTA - 1));
        }
        float xcol = 0.f;
        if (lane == 0 && warp < OUT_COLS) xcol = __bfloat162float(x[cta * OUT_COLS + warp]);
        float xv[3];
#pragma unroll
        for (int j = 0; j < 3; j++) xv[j] = (tid + 256 * j < D_MODEL) ? __bfloat162float(x[tid + 256 * j]) : 0.f;
        {
            float s = warp_sum(xv[0] + xv[1] + xv[2]);
            if (lane == 0) misc[warp] = s;
            cbar();
            float tot = 0.f;
#pragma unroll
            for (int w = 0; w < 8; w++) tot += misc[w];
            const float mean = tot * (1.0f / D_MODEL);
            float ss = 0.f;
#pragma unroll
            for (int j = 0; j < 3; j++) {
                const float d = (tid + 256 * j < D_MODEL) ? xv[j] - mean : 0.f;
                ss = fmaf(d, d, ss);
            }
            ss = warp_sum(ss);
            if (lane == 0) misc[8 + warp] = ss;
            cbar();
            float tss = 0.f;
#pragma unroll
            for (int w = 0; w < 8; w++) tss += misc[8 + w];
            const float m_bf = bfr(mean);
            const float v_bf = bfr(tss * (1.0f / D_MODEL));
            const float den = bfr(__fsqrt_rn(bfr(v_bf + 1e-5f)));
#pragma unroll 1
            for (int j = 0; j < 3; j++) {
                const float xj = j == 0 ? xv[0] : (j == 1 ? xv[1] : xv[2]);
                if (tid + 256 * j < D_MODEL) xn_s[tid + 256 * j] = bfr(__fdiv_rn(bfr(xj - m_bf), den));
            }
        }
        const unsigned int arrive_base = __float_as_uint(misc[63]);
        const uint32_t tag = (arrive_base >> 7) % 65535u + 1u;
        asm volatile("cp.async.wait_all;" ::: "memory");
        cbar();
        TL(8);
        {
            float qa[8];
#pragma unroll
            for (int i = 0; i < 8; i++) qa[i] = 0.f;
            const unsigned char* wp = smem + OFF_WO + tid * 16;
#pragma unroll 2
            for (int i = 0; i < 10; i++)
                fma8(qa, xn_s[i * 64 + (tid >> 2)], *reinterpret_cast<const uint4*>(wp + i * 4096));
#pragma unroll
            for (int i = 0; i < 8; i++) {
                qa[i] += __shfl_xor_sync(0xffffffffu, qa[i], 4);
                qa[i] += __shfl_xor_sync(0xffffffffu, qa[i], 8);
                qa[i] += __shfl_xor_sync(0xffffffffu, qa[i], 16);
            }
            if (lane < 4) {
                *reinterpret_cast<float4*>(&red[warp * 32 + lane * 8]) = make_float4(qa[0], qa[1], qa[2], qa[3]);
                *reinterpret_cast<float4*>(&red[warp * 32 + lane * 8 + 4]) = make_float4(qa[4], qa[5], qa[6], qa[7]);
            }
        }
        cbar();
        if (warp == 0) {
            float s = 0.f;
#pragma unroll
            for (int w = 0; w < 8; w++) s += red[w * 32 + lane];
            const uint32_t wrd = (__float_as_uint(bfr(s)) & 0xffff0000u) | tag;
            asm volatile("st.relaxed.gpu.global.u32 [%0], %1;" ::"l"(&g->q[cta * WO_ROWS + lane]), "r"(wrd) : "memory");
            uint32_t w0, w1_, w2_, w3;
            int it = 0;
            while (true) {
                asm volatile("ld.relaxed.gpu.global.v4.u32 {%0,%1,%2,%3}, [%4];"
                             : "=r"(w0), "=r"(w1_), "=r"(w2_), "=r"(w3)
                             : "l"(&g->q[head * DH + lane * 4])
                             : "memory");
                if ((((w0 ^ tag) | (w1_ ^ tag) | (w2_ ^ tag) | (w3 ^ tag)) & 0xffffu) == 0u) break;
                __nanosleep(40);
                if (++it > (1 << 22)) __trap();
            }
            *reinterpret_cast<uint4*>(&q_s[lane * 4]) =
                make_uint4(w0 & 0xffff0000u, w1_ & 0xffff0000u, w2_ & 0xffff0000u, w3 & 0xffff0000u);
        }
        cbar();
        float q[8];
        {
            const float4 qa = *reinterpret_cast<const float4*>(&q_s[(lane & 15) * 8]);
            const float4 qb = *reinterpret_cast<const float4*>(&q_s[(lane & 15) * 8 + 4]);
            q[0] = qa.x; q[1] = qa.y; q[2] = qa.z; q[3] = qa.w;
            q[4] = qb.x; q[5] = qb.y; q[6] = qb.z; q[7] = qb.w;
        }

        TL(1);
        const float scale = 0.08838834764831845f;
        const unsigned char* ring = smem + OFF_RING;
        int s = 0;
        uint32_t ph = 0;
        float mrun = -INFINITY, lrun = 0.f;
        const int lane_off = (warp * 8 + (lane >> 4)) * (DH * 2) + (lane & 15) * 16;
        const bool l3 = lane & 8, l2 = lane & 4;
        const int key_off = warp * 8 + 2 * ((l3 ? 2 : 0) + (l2 ? 1 : 0)) + (lane >> 4);
#pragma unroll 1
        for (int t = 0; t < NT; t++) {
            mbar_wait(bar_full + s * 8, ph);
            const unsigned char* tp = ring + s * TILE_BYTES + lane_off;
            uint4 kv[4];
#pragma unroll
            for (int j = 0; j < 4; j++) kv[j] = *reinterpret_cast<const uint4*>(tp + j * 2 * (DH * 2));
            float a0 = dot8(q, kv[0]), a1 = dot8(q, kv[1]), a2 = dot8(q, kv[2]), a3 = dot8(q, kv[3]);
            __syncwarp();
            if (lane == 0) mbar_arrive(bar_empty + s * 8);
            float s0 = l3 ? a0 : a2, s1 = l3 ? a1 : a3;
            float k0 = l3 ? a2 : a0, k1 = l3 ? a3 : a1;
            k0 += __shfl_xor_sync(0xffffffffu, s0, 8);
            k1 += __shfl_xor_sync(0xffffffffu, s1, 8);
            float sn = l2 ? k0 : k1, kp = l2 ? k1 : k0;
            kp += __shfl_xor_sync(0xffffffffu, sn, 4);
            kp += __shfl_xor_sync(0xffffffffu, kp, 2);
            kp += __shfl_xor_sync(0xffffffffu, kp, 1);
            const float sv = bfr(bfr(kp) * scale);
            const float mnew = fmaxf(mrun, sv);
            lrun = lrun * ex2((mrun - mnew) * L2E) + ex2((sv - mnew) * L2E);
            mrun = mnew;
            if ((lane & 3) == 0) sc[t * TILE + key_off] = sv;
            if (++s == STAGES) { s = 0; ph ^= 1; }
        }

        TL(2);
        {
            if (lane & 3) lrun = 0.f;
#pragma unroll 1
            for (int o = 16; o > 0; o >>= 1) ml_merge(mrun, lrun, o);
            if (lane == 0) { misc[16 + warp] = mrun; misc[24 + warp] = lrun; }
            cbar();
            if (warp == 0) {
                float m = (lane < 8) ? misc[16 + lane] : -INFINITY;
                float l = (lane < 8) ? misc[24 + lane] : 0.f;
#pragma unroll 1
                for (int o = 4; o > 0; o >>= 1) ml_merge(m, l, o);
                if (lane == 0) {
                    unsigned long long pk =
                        ((unsigned long long)__float_as_uint(l) << 32) | (__float_as_uint(m) & 0xffff0000u) | tag;
                    asm volatile("st.relaxed.gpu.global.u64 [%0], %1;" ::"l"(&g->ml[cta]), "l"(pk) : "memory");
                }
                m = -INFINITY;
                l = 0.f;
                if (lane < NSPLIT) {
                    unsigned long long pk;
                    int it = 0;
                    do {
                        asm volatile("ld.relaxed.gpu.global.u64 %0, [%1];" : "=l"(pk) : "l"(&g->ml[(cta & ~3) + lane]) : "memory");
                        if (++it > (1 << 24)) __trap();
                    } while (((uint32_t)pk & 0xffffu) != tag);
                    m = __uint_as_float((uint32_t)pk & 0xffff0000u);
                    l = __uint_as_float((uint32_t)(pk >> 32));
                }
#pragma unroll 1
                for (int o = 2; o > 0; o >>= 1) ml_merge(m, l, o);
                if (lane == 0) { misc[32] = m; misc[33] = __fdiv_rn(1.0f, l); }
            }
            cbar();
        }
        const float mg = misc[32], inv_l = misc[33];

        TL(3);
        float oa[8];
#pragma unroll
        for (int i = 0; i < 8; i++) oa[i] = 0.f;
        const int pkey = warp * 8 + (lane >> 4);
#pragma unroll 1
        for (int t = 0; t < NT; t++) {
            float p[4];
#pragma unroll
            for (int j = 0; j < 4; j++) p[j] = bfr(ex2((sc[t * TILE + pkey + 2 * j] - mg) * L2E) * inv_l);
            mbar_wait(bar_full + s * 8, ph);
            const unsigned char* tp = ring + s * TILE_BYTES + lane_off;
            uint4 vv[4];
#pragma unroll
            for (int j = 0; j < 4; j++) vv[j] = *reinterpret_cast<const uint4*>(tp + j * 2 * (DH * 2));
#pragma unroll
            for (int j = 0; j < 4; j++) fma8(oa, p[j], vv[j]);
            __syncwarp();
            if (lane == 0) mbar_arrive(bar_empty + s * 8);
            if (++s == STAGES) { s = 0; ph ^= 1; }
        }
        TL(4);

#pragma unroll
        for (int i = 0; i < 8; i++) oa[i] += __shfl_xor_sync(0xffffffffu, oa[i], 16);
        if (lane < 16) {
            *reinterpret_cast<float4*>(&red[warp * DH + lane * 8]) = make_float4(oa[0], oa[1], oa[2], oa[3]);
            *reinterpret_cast<float4*>(&red[warp * DH + lane * 8 + 4]) = make_float4(oa[4], oa[5], oa[6], oa[7]);
        }
        cbar();
        if (tid < DH) {
            float v = 0.f;
#pragma unroll
            for (int w = 0; w < 8; w++) v += red[w * DH + tid];
            asm volatile("st.relaxed.gpu.global.u64 [%0], %1;" ::"l"(&g->op[cta * DH + tid]), "l"(pack_tagged(v, tag)) : "memory");
        }
        if (warp == 0) {
            const unsigned long long* opw = &g->op[(cta & ~3) * DH + split * WO_ROWS + lane];
            float v[NSPLIT];
            int it = 0;
            while (true) {
                uint32_t bad = 0u;
#pragma unroll
                for (int j = 0; j < NSPLIT; j++) {
                    uint32_t t;
                    ld_tagged(opw + j * DH, v[j], t);
                    bad |= t ^ tag;
                }
                if (!bad) break;
                __nanosleep(100);
                if (++it > (1 << 22)) __trap();
            }
            q_s[lane] = bfr((v[0] + v[1]) + (v[2] + v[3]));
        }
        mbar_wait(bar_wo, 0);
        cbar();
        TL(5);
        if (tid < 160) {
            float a0 = 0.f, a1 = 0.f, a2 = 0.f, a3 = 0.f;
            const unsigned char* wp = smem + OFF_WO + tid * 8;
#pragma unroll 1
            for (int r4 = 0; r4 < WO_ROWS / 4; r4++) {
                const float4 ov = *reinterpret_cast<const float4*>(&q_s[r4 * 4]);
                const float ovv[4] = {ov.x, ov.y, ov.z, ov.w};
#pragma unroll
                for (int k = 0; k < 4; k++) {
                    const uint2 w = *reinterpret_cast<const uint2*>(wp + (r4 * 4 + k) * (D_MODEL * 2));
                    a0 = fmaf(ovv[k], bflo(w.x), a0);
                    a1 = fmaf(ovv[k], bfhi(w.x), a1);
                    a2 = fmaf(ovv[k], bflo(w.y), a2);
                    a3 = fmaf(ovv[k], bfhi(w.y), a3);
                }
            }
            unsigned long long* dst = &g->outA[cta * D_MODEL + tid * 4];
            asm volatile("st.relaxed.gpu.global.v2.u64 [%0], {%1, %2};" ::"l"(dst), "l"(pack_tagged(a0, tag)), "l"(pack_tagged(a1, tag))
                         : "memory");
            asm volatile("st.relaxed.gpu.global.v2.u64 [%0], {%1, %2};" ::"l"(dst + 2), "l"(pack_tagged(a2, tag)),
                         "l"(pack_tagged(a3, tag))
                         : "memory");
        }
        if (tid == 255) asm volatile("red.relaxed.gpu.global.add.u32 [%0], %1;" ::"l"(&g->arrive), "r"(1u) : "memory");
        TL(6);
        {
            const unsigned long long* src = &g->outA[(tid & (NCTA - 1)) * D_MODEL + cta * OUT_COLS];
            uint32_t ok = tid < NCTA ? 0u : 1u;
            int it = 0;
            while (true) {
                if (!ok) {
                    uint32_t bad = 0u;
#pragma unroll
                    for (int k = 0; k < OUT_COLS; k++) {
                        float v;
                        uint32_t t;
                        ld_tagged(src + k, v, t);
                        red[k * NCTA + tid] = v;
                        bad |= t ^ tag;
                    }
                    ok = bad == 0u;
                }
                uint32_t all;
                asm volatile(
                    "{\n.reg .pred p, q;\nsetp.ne.u32 p, %1, 0;\nbar.red.and.pred q, 1, 256, p;\nselp.u32 %0, 1, 0, q;\n}"
                    : "=r"(all)
                    : "r"(ok)
                    : "memory");
                if (all) break;
                if (tid == 0) {
                    unsigned int cnt;
                    int it2 = 0;
                    while (true) {
                        asm volatile("ld.relaxed.gpu.global.u32 %0, [%1];" : "=r"(cnt) : "l"(&g->arrive) : "memory");
                        if (cnt - arrive_base >= (unsigned)(NCTA - GATE_SLACK)) break;
                        __nanosleep(100);
                        if (++it2 > (1 << 22)) __trap();
                    }
                }
                cbar();
                if (++it > (1 << 22)) __trap();
            }
        }
        TL(10);
        asm volatile("bar.sync 3, 288;" ::: "memory");
        if (warp < OUT_COLS) {
            const float* rp = red + warp * NCTA + lane;
            const float a = bfr(warp_sum((rp[0] + rp[32]) + (rp[64] + rp[96])));
            if (lane == 0) out[cta * OUT_COLS + warp] = __float2bfloat16_rn(bfr(xcol + a) + misc[40 + warp]);
        }
        TL(7);
    }
}

}

extern "C" void kernel_launch(void* const* d_in, const int* in_sizes, int n_in, void* d_out, int out_size) {
    const __nv_bfloat16* x = (const __nv_bfloat16*)d_in[0];
    const __nv_bfloat16* kc = (const __nv_bfloat16*)d_in[1];
    const __nv_bfloat16* vc = (const __nv_bfloat16*)d_in[2];
    const __nv_bfloat16* wq = (const __nv_bfloat16*)d_in[3];
    const __nv_bfloat16* wo = (const __nv_bfloat16*)d_in[4];
    const __nv_bfloat16* w1 = (const __nv_bfloat16*)d_in[6];
    const __nv_bfloat16* b1 = (const __nv_bfloat16*)d_in[7];
    const __nv_bfloat16* w2 = (const __nv_bfloat16*)d_in[8];
    const __nv_bfloat16* b2 = (const __nv_bfloat16*)d_in[9];
    static bool attr_set = false;
    if (!attr_set) {
        cudaFuncSetAttribute(fused_decode_kernel, cudaFuncAttributeMaxDynamicSharedMemorySize, SMEM_BYTES);
        attr_set = true;
    }
    fused_decode_kernel<<<NCTA, NTHREADS, SMEM_BYTES>>>(x, kc, vc, wq, wo, w1, b1, w2, b2, (__nv_bfloat16*)d_out);
}
```

```cpp
#include <cuda_runtime.h>
#include <cuda_bf16.h>
#include <stdint.h>

namespace {

constexpr int D_MODEL = 640;
constexpr int NHEAD = 32;
constexpr int SK = 16384;
constexpr int DH = 128;
constexpr int FF = 1728;
constexpr int NSPLIT = 4;
constexpr int NCTA = NHEAD * NSPLIT;
constexpr int KEYS_PER_CTA = SK / NSPLIT;
constexpr int TILE = 64;
constexpr int TILE_BYTES = TILE * DH * 2;
constexpr int NT = KEYS_PER_CTA / TILE;
constexpr int STAGES = 10;
#define INFLIGHT_N 4
constexpr int INFLIGHT = INFLIGHT_N;
constexpr int WO_ROWS = DH / NSPLIT;
constexpr int WO_BYTES = WO_ROWS * D_MODEL * 2;
constexpr int WO_COLS = D_MODEL / NSPLIT;
constexpr int MLP_COLS = 32;
constexpr int MLP_CTAS = FF / MLP_COLS;
constexpr int OUT_COLS = D_MODEL / NCTA;
constexpr int NTHREADS = 320;
constexpr int PACE_START = 84, PACE_LO = 2;
#define GATE_SLACK 4

constexpr int OFF_RING = 0;
constexpr int OFF_WO = OFF_RING + STAGES * TILE_BYTES;
constexpr int OFF_SC = OFF_WO + WO_BYTES;
constexpr int OFF_XN = OFF_SC + KEYS_PER_CTA * 4;
constexpr int OFF_Y = OFF_XN + D_MODEL * 4;
constexpr int OFF_RED = OFF_Y + D_MODEL * 4;
constexpr int OFF_Q = OFF_RED + 8 * DH * 4;
constexpr int OFF_MISC = OFF_Q + DH * 4;
constexpr int OFF_BAR = OFF_MISC + 256;
constexpr int SMEM_BYTES = OFF_BAR + 2 * STAGES * 8;

struct alignas(256) Scratch {
    uint32_t q[NHEAD * DH];
    unsigned long long ml[NCTA];
    unsigned long long op[NCTA * DH];
    unsigned long long outA[NHEAD * D_MODEL];
    float accB[D_MODEL];
    unsigned int cntB;
    unsigned int arrive;
    alignas(128) unsigned int prog;
};
__device__ Scratch g_scr;

#define TL(i) do { } while (0)

__device__ __forceinline__ uint32_t s2u(const void* p) { return (uint32_t)__cvta_generic_to_shared(p); }
__device__ __forceinline__ void mbar_init(uint32_t a, uint32_t c) {
    asm volatile("mbarrier.init.shared::cta.b64 [%0], %1;" ::"r"(a), "r"(c));
}
__device__ __forceinline__ void mbar_expect(uint32_t a, uint32_t b) {
    asm volatile("mbarrier.arrive.expect_tx.shared::cta.b64 _, [%0], %1;" ::"r"(a), "r"(b) : "memory");
}
__device__ __forceinline__ void mbar_arrive(uint32_t a) {
    asm volatile("mbarrier.arrive.shared::cta.b64 _, [%0];" ::"r"(a) : "memory");
}
__device__ __forceinline__ void mbar_wait(uint32_t a, uint32_t ph) {
    uint32_t ok;
    int it = 0;
    do {
        asm volatile(
            "{\n.reg .pred p;\nmbarrier.try_wait.parity.shared::cta.b64 p, [%1], %2;\nselp.u32 %0,1,0,p;\n}"
            : "=r"(ok)
            : "r"(a), "r"(ph)
            : "memory");
        if (++it > (1 << 22)) __trap();
    } while (!ok);
}
__device__ __forceinline__ void bulk_g2s_hint(uint32_t dst, const void* src, uint32_t bytes, uint32_t bar, uint64_t pol) {
    asm volatile("cp.async.bulk.shared::cluster.global.mbarrier::complete_tx::bytes.L2::cache_hint [%0], [%1], %2, [%3], %4;" ::"r"(dst),
                 "l"(src), "r"(bytes), "r"(bar), "l"(pol)
                 : "memory");
}
__device__ __forceinline__ void cbar() { asm volatile("bar.sync 1, 256;" ::: "memory"); }

__device__ __forceinline__ float bfr(float x) { return __bfloat162float(__float2bfloat16_rn(x)); }
__device__ __forceinline__ float bflo(uint32_t u) { return __uint_as_float(u << 16); }
__device__ __forceinline__ float bfhi(uint32_t u) { return __uint_as_float(u & 0xffff0000u); }
__device__ __forceinline__ float ex2(float x) {
    float r;
    asm("ex2.approx.ftz.f32 %0, %1;" : "=f"(r) : "f"(x));
    return r;
}

__device__ __forceinline__ uint4 ldg_nc16(const void* p) {
    uint4 v;
    asm volatile("ld.global.nc.L1::no_allocate.v4.u32 {%0,%1,%2,%3}, [%4];"
                 : "=r"(v.x), "=r"(v.y), "=r"(v.z), "=r"(v.w)
                 : "l"(p));
    return v;
}
__device__ __forceinline__ uint2 ldg_nc8(const void* p) {
    uint2 v;
    asm volatile("ld.global.nc.L1::no_allocate.v2.u32 {%0,%1}, [%2];" : "=r"(v.x), "=r"(v.y) : "l"(p));
    return v;
}
__device__ __forceinline__ unsigned long long pack_tagged(float v, uint32_t tag) {
    return ((unsigned long long)tag << 32) | __float_as_uint(v);
}
__device__ __forceinline__ void ld_tagged(const unsigned long long* p, float& v, uint32_t& t) {
    unsigned long long w;
    asm volatile("ld.relaxed.gpu.global.u64 %0, [%1];" : "=l"(w) : "l"(p) : "memory");
    v = __uint_as_float((uint32_t)w);
    t = (uint32_t)(w >> 32);
}
__device__ __forceinline__ float warp_sum(float v) {
#pragma unroll
    for (int o = 16; o > 0; o >>= 1) v += __shfl_xor_sync(0xffffffffu, v, o);
    return v;
}

__device__ __forceinline__ void fma8(float* acc, float s, const uint4& v) {
    acc[0] = fmaf(s, bflo(v.x), acc[0]);
    acc[1] = fmaf(s, bfhi(v.x), acc[1]);
    acc[2] = fmaf(s, bflo(v.y), acc[2]);
    acc[3] = fmaf(s, bfhi(v.y), acc[3]);
    acc[4] = fmaf(s, bflo(v.z), acc[4]);
    acc[5] = fmaf(s, bfhi(v.z), acc[5]);
    acc[6] = fmaf(s, bflo(v.w), acc[6]);
    acc[7] = fmaf(s, bfhi(v.w), acc[7]);
}
__device__ __forceinline__ float dot8(const float* q, const uint4& v) {
    float a = q[0] * bflo(v.x);
    float b = q[1] * bfhi(v.x);
    a = fmaf(q[2], bflo(v.y), a);
    b = fmaf(q[3], bfhi(v.y), b);
    a = fmaf(q[4], bflo(v.z), a);
    b = fmaf(q[5], bfhi(v.z), b);
    a = fmaf(q[6], bflo(v.w), a);
    b = fmaf(q[7], bfhi(v.w), b);
    return a + b;
}

__device__ __noinline__ void warp_layernorm(float* v) {
    float s = 0.f;
#pragma unroll
    for (int i = 0; i < 20; i++) s += v[i];
    s = warp_sum(s);
    const float mean = s * (1.0f / D_MODEL);
    float ss = 0.f;
#pragma unroll
    for (int i = 0; i < 20; i++) {
        float d = v[i] - mean;
        ss = fmaf(d, d, ss);
    }
    ss = warp_sum(ss);
    const float m_bf = bfr(mean);
    const float v_bf = bfr(ss * (1.0f / D_MODEL));
    const float den = bfr(sqrtf(bfr(v_bf + 1e-5f)));
#pragma unroll
    for (int i = 0; i < 20; i++) v[i] = bfr(__fdiv_rn(bfr(v[i] - m_bf), den));
}

constexpr float L2E = 1.4426950408889634f;

__device__ __forceinline__ void ml_merge(float& m, float& l, int o) {
    const float mo = __shfl_xor_sync(0xffffffffu, m, o);
    const float lo = __shfl_xor_sync(0xffffffffu, l, o);
    const float mn = fmaxf(m, mo);
    l = l * ex2((m - mn) * L2E) + lo * ex2((mo - mn) * L2E);
    m = mn;
}

__global__ void __launch_bounds__(NTHREADS, 1)
fused_decode_kernel(const __nv_bfloat16* __restrict__ x, const __nv_bfloat16* __restrict__ kc,
                    const __nv_bfloat16* __restrict__ vc, const __nv_bfloat16* __restrict__ wq,
                    const __nv_bfloat16* __restrict__ wo, const __nv_bfloat16* __restrict__ w1,
                    const __nv_bfloat16* __restrict__ b1, const __nv_bfloat16* __restrict__ w2,
                    const __nv_bfloat16* __restrict__ b2, __nv_bfloat16* __restrict__ out) {
    extern __shared__ __align__(1024) unsigned char smem[];
    const int tid = threadIdx.x, warp = tid >> 5, lane = tid & 31;
    const int cta = blockIdx.x, head = cta >> 2, split = cta & 3;
    Scratch* const g = &g_scr;

    float* sc = reinterpret_cast<float*>(smem + OFF_SC);
    float* xn_s = reinterpret_cast<float*>(smem + OFF_XN);
    float* q_s = reinterpret_cast<float*>(smem + OFF_Q);
    float* red = reinterpret_cast<float*>(smem + OFF_RED);
    float* misc = reinterpret_cast<float*>(smem + OFF_MISC);
    const uint32_t bar_full = s2u(smem + OFF_BAR);
    const uint32_t bar_empty = bar_full + STAGES * 8;

    TL(0);
    if (warp == 8) {
        if (lane == 0) { misc[61] = __int_as_float(INFLIGHT); misc[62] = __int_as_float(INFLIGHT); }
        if (lane < 2 * STAGES) mbar_init(bar_full + lane * 8, lane >= STAGES ? 8 : 1);
        asm volatile("fence.mbarrier_init.release.cluster;" ::: "memory");
        __syncwarp();
        if (lane == 0) {
            uint64_t pol;
            asm volatile("createpolicy.fractional.L2::evict_first.b64 %0, 1.0;" : "=l"(pol));
            const unsigned char* kb =
                reinterpret_cast<const unsigned char*>(kc) + (size_t)head * SK * (DH * 2) + (size_t)split * TILE_BYTES;
#pragma unroll 1
            for (int t = 0; t < INFLIGHT; t++) {
                mbar_expect(bar_full + t * 8, TILE_BYTES);
                bulk_g2s_hint(s2u(smem + OFF_RING) + t * TILE_BYTES, kb + (size_t)t * (NSPLIT * TILE_BYTES), TILE_BYTES,
                              bar_full + t * 8, pol);
            }
        }
    } else if (warp < 8) {
        const unsigned char* wqp = reinterpret_cast<const unsigned char*>(wq) + (size_t)(head * DH + split * WO_ROWS) * 2 +
                                   (tid & 3) * 16 + (size_t)(tid >> 2) * (NHEAD * DH * 2);
        uint32_t dst = s2u(smem + OFF_WO) + tid * 16;
#pragma unroll 1
        for (int i = 0; i < 10; i++) {
            asm volatile("cp.async.cg.shared.global [%0], [%1], 16;" ::"r"(dst), "l"(wqp) : "memory");
            dst += 4096;
            wqp += (size_t)64 * (NHEAD * DH * 2);
        }
        asm volatile("cp.async.commit_group;" ::: "memory");
    }
    __syncthreads();

    if (warp == 8) {
        if (lane == 0) {
            const unsigned char* kbase =
                reinterpret_cast<const unsigned char*>(kc) + (size_t)head * SK * (DH * 2) + (size_t)split * TILE_BYTES;
            const unsigned char* vbase =
                reinterpret_cast<const unsigned char*>(vc) + (size_t)head * SK * (DH * 2) + (size_t)split * TILE_BYTES;
            const uint32_t ring = s2u(smem + OFF_RING);
            int s = INFLIGHT, sl = 0, nl = 0, infl = INFLIGHT;
            uint32_t ph = 1, phl = 0;
            uint64_t pol;
            asm volatile("createpolicy.fractional.L2::evict_first.b64 %0, 1.0;" : "=l"(pol));
#pragma unroll 1
            for (int t = INFLIGHT; t < 2 * NT; t++) {
#pragma unroll 1
                while (t - nl >= infl) {
                    mbar_wait(bar_full + sl * 8, phl);
                    if (++sl == STAGES) { sl = 0; phl ^= 1; }
                    nl++;
                }
                mbar_wait(bar_empty + s * 8, ph);
                mbar_expect(bar_full + s * 8, TILE_BYTES);
                const unsigned char* src =
                    (t < NT) ? (kbase + (size_t)t * (NSPLIT * TILE_BYTES)) : (vbase + (size_t)(t - NT) * (NSPLIT * TILE_BYTES));
                bulk_g2s_hint(ring + s * TILE_BYTES, src, TILE_BYTES, bar_full + s * 8, pol);
                asm volatile("st.volatile.shared.u32 [%0], %1;" ::"r"(s2u(misc + 61)), "r"(t + 1) : "memory");
                asm volatile("ld.volatile.shared.u32 %0, [%1];" : "=r"(infl) : "r"(s2u(misc + 62)) : "memory");
                if (++s == STAGES) { s = 0; ph ^= 1; }
            }
        }
    } else if (warp == 9) {
        unsigned int bbase;
        asm volatile("ld.relaxed.gpu.global.u32 %0, [%1];" : "=r"(bbase) : "l"(&g->cntB) : "memory");
        bbase &= ~(unsigned)(NCTA - 1);
        if (cta < MLP_CTAS) {
            const int f0 = cta * MLP_COLS;
            float* y_s = reinterpret_cast<float*>(smem + OFF_Y);
            {
                float v[20];
#pragma unroll
                for (int i = 0; i < 20; i++) v[i] = __bfloat162float(x[lane + 32 * i]);
                warp_layernorm(v);
                warp_layernorm(v);
#pragma unroll
                for (int i = 0; i < 20; i++) y_s[lane + 32 * i] = v[i];
            }
            __syncwarp();
            float acc[8];
#pragma unroll
            for (int i = 0; i < 8; i++) acc[i] = 0.f;
            const unsigned char* w1p =
                reinterpret_cast<const unsigned char*>(w1) + (size_t)f0 * 2 + (lane & 3) * 16 + (size_t)(lane >> 2) * (FF * 2);
#pragma unroll 1
            for (int b = 0; b < 8; b++) {
                uint4 wv[10];
#pragma unroll
                for (int i = 0; i < 10; i++) wv[i] = ldg_nc16(w1p + (size_t)((b * 10 + i) * 8) * (FF * 2));
#pragma unroll
                for (int i = 0; i < 10; i++) fma8(acc, y_s[(b * 10 + i) * 8 + (lane >> 2)], wv[i]);
            }
#pragma unroll
            for (int i = 0; i < 8; i++) {
#pragma unroll
                for (int o = 4; o <= 16; o <<= 1) acc[i] += __shfl_xor_sync(0xffffffffu, acc[i], o);
            }
            float hval[8];
#pragma unroll
            for (int i = 0; i < 8; i++) {
                const int f = f0 + (lane & 3) * 8 + i;
                const float pre = bfr(bfr(acc[i]) + __bfloat162float(b1[f]));
                const float inner = 0.7978845608028654f * (pre + 0.044715f * pre * pre * pre);
                hval[i] = bfr(0.5f * pre * (1.0f + tanhf(inner)));
            }
            float o[20];
#pragma unroll
            for (int i = 0; i < 20; i++) o[i] = 0.f;
            const unsigned char* w2p = reinterpret_cast<const unsigned char*>(w2) + (size_t)f0 * (D_MODEL * 2) + lane * 8;
#pragma unroll 1
            for (int rb = 0; rb < 4; rb++) {
                uint2 wv[8][5];
#pragma unroll
                for (int r = 0; r < 8; r++)
#pragma unroll
                    for (int i = 0; i < 5; i++) wv[r][i] = ldg_nc8(w2p + (size_t)(rb * 8 + r) * (D_MODEL * 2) + i * 256);
#pragma unroll
                for (int r = 0; r < 8; r++) {
                    const float hv = __shfl_sync(0xffffffffu, hval[r], rb);
#pragma unroll
                    for (int i = 0; i < 5; i++) {
                        o[i * 4 + 0] = fmaf(hv, bflo(wv[r][i].x), o[i * 4 + 0]);
                        o[i * 4 + 1] = fmaf(hv, bfhi(wv[r][i].x), o[i * 4 + 1]);
                        o[i * 4 + 2] = fmaf(hv, bflo(wv[r][i].y), o[i * 4 + 2]);
                        o[i * 4 + 3] = fmaf(hv, bfhi(wv[r][i].y), o[i * 4 + 3]);
                    }
                }
            }
#pragma unroll
            for (int i = 0; i < 5; i++)
#pragma unroll
                for (int j = 0; j < 4; j++) atomicAdd(&g->accB[(lane + 32 * i) * 4 + j], o[i * 4 + j]);
            __threadfence();
            __syncwarp();
        }
        if (lane == 0) atomicAdd(&g->cntB, 1u);
        mbar_wait(bar_empty + (STAGES - 1) * 8, 0);
        mbar_wait(bar_empty + (STAGES - 1) * 8, 1);
        if (lane < OUT_COLS) {
            unsigned int c;
            int it = 0;
            while (true) {
                asm volatile("ld.acquire.gpu.global.u32 %0, [%1];" : "=r"(c) : "l"(&g->cntB) : "memory");
                if (c - bbase >= (unsigned)NCTA) break;
                __nanosleep(1000);
                if (++it > (1 << 22)) __trap();
            }
            float* ap = &g->accB[cta * OUT_COLS + lane];
            const float b = __ldcg(ap);
            __stcg(ap, 0.f);
            misc[40 + lane] = bfr(bfr(b) + __bfloat162float(b2[cta * OUT_COLS + lane]));
        }
        __syncwarp();
        asm volatile("bar.arrive 3, 288;" ::: "memory");
        if (lane == 0) {
            int last = 0;
#pragma unroll 1
            for (int it = 0; it < (1 << 22); it++) {
                int t;
                asm volatile("ld.volatile.shared.u32 %0, [%1];" : "=r"(t) : "r"(s2u(misc + 61)) : "memory");
                if (t != last) asm volatile("red.relaxed.gpu.global.add.u32 [%0], %1;" ::"l"(&g->prog), "r"(t - last) : "memory");
                last = t;
                if (t >= 2 * NT) break;
                uint32_t pv;
                asm volatile("ld.relaxed.gpu.global.u32 %0, [%1];" : "=r"(pv) : "l"(&g->prog) : "memory");
                const int d = t - (int)((pv & (unsigned)(NCTA * 2 * NT - 1)) >> 7);
                const int nf = t < PACE_START ? INFLIGHT : min(STAGES, max(PACE_LO, INFLIGHT - d));
                asm volatile("st.volatile.shared.u32 [%0], %1;" ::"r"(s2u(misc + 62)), "r"(nf) : "memory");
                __nanosleep(500);
            }
        }
    } else {
        if (tid == 0) {
            unsigned int a;
            asm volatile("ld.relaxed.gpu.global.u32 %0, [%1];" : "=r"(a) : "l"(&g->arrive) : "memory");
            misc[63] = __uint_as_float(a & ~(unsigned)(NCTA - 1));
        }
        float xcol = 0.f;
        if (lane == 0 && warp < OUT_COLS) xcol = __bfloat162float(x[cta * OUT_COLS + warp]);
        float xv[3];
#pragma unroll
        for (int j = 0; j < 3; j++) xv[j] = (tid + 256 * j < D_MODEL) ? __bfloat162float(x[tid + 256 * j]) : 0.f;
        {
            float s = warp_sum(xv[0] + xv[1] + xv[2]);
            if (lane == 0) misc[warp] = s;
            cbar();
            float tot = 0.f;
#pragma unroll
            for (int w = 0; w < 8; w++) tot += misc[w];
            const float mean = tot * (1.0f / D_MODEL);
            float ss = 0.f;
#pragma unroll
            for (int j = 0; j < 3; j++) {
                const float d = (tid + 256 * j < D_MODEL) ? xv[j] - mean : 0.f;
                ss = fmaf(d, d, ss);
            }
            ss = warp_sum(ss);
            if (lane == 0) misc[8 + warp] = ss;
            cbar();
            float tss = 0.f;
#pragma unroll
            for (int w = 0; w < 8; w++) tss += misc[8 + w];
            const float m_bf = bfr(mean);
            const float v_bf = bfr(tss * (1.0f / D_MODEL));
            const float den = bfr(__fsqrt_rn(bfr(v_bf + 1e-5f)));
#pragma unroll 1
            for (int j = 0; j < 3; j++) {
                const float xj = j == 0 ? xv[0] : (j == 1 ? xv[1] : xv[2]);
                if (tid + 256 * j < D_MODEL) xn_s[tid + 256 * j] = bfr(__fdiv_rn(bfr(xj - m_bf), den));
            }
        }
        const unsigned int arrive_base = __float_as_uint(misc[63]);
        const uint32_t tag = (arrive_base >> 7) % 65535u + 1u;
        asm volatile("cp.async.wait_all;" ::: "memory");
        cbar();
        TL(8);
        {
            float qa[8];
#pragma unroll
            for (int i = 0; i < 8; i++) qa[i] = 0.f;
            const unsigned char* wp = smem + OFF_WO + tid * 16;
#pragma unroll 2
            for (int i = 0; i < 10; i++)
                fma8(qa, xn_s[i * 64 + (tid >> 2)], *reinterpret_cast<const uint4*>(wp + i * 4096));
#pragma unroll
            for (int i = 0; i < 8; i++) {
                qa[i] += __shfl_xor_sync(0xffffffffu, qa[i], 4);
                qa[i] += __shfl_xor_sync(0xffffffffu, qa[i], 8);
                qa[i] += __shfl_xor_sync(0xffffffffu, qa[i], 16);
            }
            if (lane < 4) {
                *reinterpret_cast<float4*>(&red[warp * 32 + lane * 8]) = make_float4(qa[0], qa[1], qa[2], qa[3]);
                *reinterpret_cast<float4*>(&red[warp * 32 + lane * 8 + 4]) = make_float4(qa[4], qa[5], qa[6], qa[7]);
            }
        }
        cbar();
        if (warp == 0) {
            float s = 0.f;
#pragma unroll
            for (int w = 0; w < 8; w++) s += red[w * 32 + lane];
            const uint32_t wrd = (__float_as_uint(bfr(s)) & 0xffff0000u) | tag;
            asm volatile("st.relaxed.gpu.global.u32 [%0], %1;" ::"l"(&g->q[cta * WO_ROWS + lane]), "r"(wrd) : "memory");
            uint32_t w0, w1_, w2_, w3;
            int it = 0;
            while (true) {
                asm volatile("ld.relaxed.gpu.global.v4.u32 {%0,%1,%2,%3}, [%4];"
                             : "=r"(w0), "=r"(w1_), "=r"(w2_), "=r"(w3)
                             : "l"(&g->q[head * DH + lane * 4])
                             : "memory");
                if ((((w0 ^ tag) | (w1_ ^ tag) | (w2_ ^ tag) | (w3 ^ tag)) & 0xffffu) == 0u) break;
                __nanosleep(40);
                if (++it > (1 << 22)) __trap();
            }
            *reinterpret_cast<uint4*>(&q_s[lane * 4]) =
                make_uint4(w0 & 0xffff0000u, w1_ & 0xffff0000u, w2_ & 0xffff0000u, w3 & 0xffff0000u);
        }
        cbar();
        {
            const unsigned char* wob = reinterpret_cast<const unsigned char*>(wo) + (size_t)head * DH * (D_MODEL * 2) + split * (WO_COLS * 2);
#pragma unroll 1
            for (int i = 0; i < 10; i++) {
                const int idx = i * 256 + tid, row = idx / 20, c = idx - row * 20;
                asm volatile("cp.async.cg.shared.global [%0], [%1], 16;" ::"r"(s2u(smem + OFF_WO) + idx * 16),
                             "l"(wob + (size_t)row * (D_MODEL * 2) + c * 16)
                             : "memory");
            }
            asm volatile("cp.async.commit_group;" ::: "memory");
        }
        float q[8];
        {
            const float4 qa = *reinterpret_cast<const float4*>(&q_s[(lane & 15) * 8]);
            const float4 qb = *reinterpret_cast<const float4*>(&q_s[(lane & 15) * 8 + 4]);
            q[0] = qa.x; q[1] = qa.y; q[2] = qa.z; q[3] = qa.w;
            q[4] = qb.x; q[5] = qb.y; q[6] = qb.z; q[7] = qb.w;
        }

        TL(1);
        const float scale = 0.08838834764831845f;
        const unsigned char* ring = smem + OFF_RING;
        int s = 0;
        uint32_t ph = 0;
        float mrun = -INFINITY, lrun = 0.f;
        const int lane_off = (warp * 8 + (lane >> 4)) * (DH * 2) + (lane & 15) * 16;
        const bool l3 = lane & 8, l2 = lane & 4;
        const int key_off = warp * 8 + 2 * ((l3 ? 2 : 0) + (l2 ? 1 : 0)) + (lane >> 4);
#pragma unroll 1
        for (int t = 0; t < NT; t++) {
            mbar_wait(bar_full + s * 8, ph);
            const unsigned char* tp = ring + s * TILE_BYTES + lane_off;
            uint4 kv[4];
#pragma unroll
            for (int j = 0; j < 4; j++) kv[j] = *reinterpret_cast<const uint4*>(tp + j * 2 * (DH * 2));
            float a0 = dot8(q, kv[0]), a1 = dot8(q, kv[1]), a2 = dot8(q, kv[2]), a3 = dot8(q, kv[3]);
            __syncwarp();
            if (lane == 0) mbar_arrive(bar_empty + s * 8);
            float s0 = l3 ? a0 : a2, s1 = l3 ? a1 : a3;
            float k0 = l3 ? a2 : a0, k1 = l3 ? a3 : a1;
            k0 += __shfl_xor_sync(0xffffffffu, s0, 8);
            k1 += __shfl_xor_sync(0xffffffffu, s1, 8);
            float sn = l2 ? k0 : k1, kp = l2 ? k1 : k0;
            kp += __shfl_xor_sync(0xffffffffu, sn, 4);
            kp += __shfl_xor_sync(0xffffffffu, kp, 2);
            kp += __shfl_xor_sync(0xffffffffu, kp, 1);
            const float sv = bfr(bfr(kp) * scale);
            const float mnew = fmaxf(mrun, sv);
            lrun = lrun * ex2((mrun - mnew) * L2E) + ex2((sv - mnew) * L2E);
            mrun = mnew;
            if ((lane & 3) == 0) sc[t * TILE + key_off] = sv;
            if (++s == STAGES) { s = 0; ph ^= 1; }
        }

        TL(2);
        {
            if (lane & 3) lrun = 0.f;
#pragma unroll 1
            for (int o = 16; o > 0; o >>= 1) ml_merge(mrun, lrun, o);
            if (lane == 0) { misc[16 + warp] = mrun; misc[24 + warp] = lrun; }
            cbar();
            if (warp == 0) {
                float m = (lane < 8) ? misc[16 + lane] : -INFINITY;
                float l = (lane < 8) ? misc[24 + lane] : 0.f;
#pragma unroll 1
                for (int o = 4; o > 0; o >>= 1) ml_merge(m, l, o);
                if (lane == 0) {
                    unsigned long long pk =
                        ((unsigned long long)__float_as_uint(l) << 32) | (__float_as_uint(m) & 0xffff0000u) | tag;
                    asm volatile("st.relaxed.gpu.global.u64 [%0], %1;" ::"l"(&g->ml[cta]), "l"(pk) : "memory");
                }
                m = -INFINITY;
                l = 0.f;
                if (lane < NSPLIT) {
                    unsigned long long pk;
                    int it = 0;
                    do {
                        asm volatile("ld.relaxed.gpu.global.u64 %0, [%1];" : "=l"(pk) : "l"(&g->ml[(cta & ~3) + lane]) : "memory");
                        if (++it > (1 << 24)) __trap();
                    } while (((uint32_t)pk & 0xffffu) != tag);
                    m = __uint_as_float((uint32_t)pk & 0xffff0000u);
                    l = __uint_as_float((uint32_t)(pk >> 32));
                }
#pragma unroll 1
                for (int o = 2; o > 0; o >>= 1) ml_merge(m, l, o);
                if (lane == 0) { misc[32] = m; misc[33] = __fdiv_rn(1.0f, l); }
            }
            cbar();
        }
        const float mg = misc[32], inv_l = misc[33];

        TL(3);
        float oa[8];
#pragma unroll
        for (int i = 0; i < 8; i++) oa[i] = 0.f;
        const int pkey = warp * 8 + (lane >> 4);
#pragma unroll 1
        for (int t = 0; t < NT; t++) {
            float p[4];
#pragma unroll
            for (int j = 0; j < 4; j++) p[j] = bfr(ex2((sc[t * TILE + pkey + 2 * j] - mg) * L2E) * inv_l);
            mbar_wait(bar_full + s * 8, ph);
            const unsigned char* tp = ring + s * TILE_BYTES + lane_off;
            uint4 vv[4];
#pragma unroll
            for (int j = 0; j < 4; j++) vv[j] = *reinterpret_cast<const uint4*>(tp + j * 2 * (DH * 2));
#pragma unroll
            for (int j = 0; j < 4; j++) fma8(oa, p[j], vv[j]);
            __syncwarp();
            if (lane == 0) mbar_arrive(bar_empty + s * 8);
            if (++s == STAGES) { s = 0; ph ^= 1; }
        }
        TL(4);

#pragma unroll
        for (int i = 0; i < 8; i++) oa[i] += __shfl_xor_sync(0xffffffffu, oa[i], 16);
        if (lane < 16) {
            *reinterpret_cast<float4*>(&red[warp * DH + lane * 8]) = make_float4(oa[0], oa[1], oa[2], oa[3]);
            *reinterpret_cast<float4*>(&red[warp * DH + lane * 8 + 4]) = make_float4(oa[4], oa[5], oa[6], oa[7]);
        }
        cbar();
        if (tid < DH) {
            float v = 0.f;
#pragma unroll
            for (int w = 0; w < 8; w++) v += red[w * DH + tid];
            asm volatile("st.relaxed.gpu.global.u64 [%0], %1;" ::"l"(&g->op[cta * DH + tid]), "l"(pack_tagged(v, tag)) : "memory");
        }
        if (tid < DH) {
            const unsigned long long* opw = &g->op[(cta & ~3) * DH + tid];
            float v[NSPLIT];
            int it = 0;
            while (true) {
                uint32_t bad = 0u;
#pragma unroll
                for (int j = 0; j < NSPLIT; j++) {
                    uint32_t t;
                    ld_tagged(opw + j * DH, v[j], t);
                    bad |= t ^ tag;
                }
                if (!bad) break;
                __nanosleep(100);
                if (++it > (1 << 22)) __trap();
            }
            q_s[tid] = bfr((v[0] + v[1]) + (v[2] + v[3]));
        }
        asm volatile("cp.async.wait_all;" ::: "memory");
        cbar();
        TL(5);
        if (lane < WO_COLS / 8) {
            float acc[8];
#pragma unroll
            for (int i = 0; i < 8; i++) acc[i] = 0.f;
            const unsigned char* wp = smem + OFF_WO + warp * 16 * (WO_COLS * 2) + lane * 16;
#pragma unroll 4
            for (int r = 0; r < 16; r++)
                fma8(acc, q_s[warp * 16 + r], *reinterpret_cast<const uint4*>(wp + r * (WO_COLS * 2)));
            float* rp = sc + warp * WO_COLS + lane * 8;
            *reinterpret_cast<float4*>(rp) = make_float4(acc[0], acc[1], acc[2], acc[3]);
            *reinterpret_cast<float4*>(rp + 4) = make_float4(acc[4], acc[5], acc[6], acc[7]);
        }
        cbar();
        if (tid < WO_COLS) {
            float v = 0.f;
#pragma unroll
            for (int w = 0; w < 8; w++) v += sc[w * WO_COLS + tid];
            asm volatile("st.relaxed.gpu.global.u64 [%0], %1;" ::"l"(&g->outA[head * D_MODEL + split * WO_COLS + tid]),
                         "l"(pack_tagged(v, tag))
                         : "memory");
        }
        if (tid == 255) asm volatile("red.relaxed.gpu.global.add.u32 [%0], %1;" ::"l"(&g->arrive), "r"(1u) : "memory");
        TL(6);
        if (tid == 0) {
            unsigned int cnt;
            int it2 = 0;
            while (true) {
                asm volatile("ld.relaxed.gpu.global.u32 %0, [%1];" : "=r"(cnt) : "l"(&g->arrive) : "memory");
                if (cnt - arrive_base >= (unsigned)(NCTA - GATE_SLACK)) break;
                __nanosleep(100);
                if (++it2 > (1 << 22)) __trap();
            }
        }
        cbar();
        if (tid < NHEAD * OUT_COLS) {
            const int hh = tid / OUT_COLS, k = tid - hh * OUT_COLS;
            const unsigned long long* src = &g->outA[hh * D_MODEL + cta * OUT_COLS + k];
            float v;
            uint32_t t;
            int it = 0;
            while (true) {
                ld_tagged(src, v, t);
                if (t == tag) break;
                if (++it > (1 << 22)) __trap();
            }
            red[k * NHEAD + hh] = v;
        }
        cbar();
        TL(10);
        asm volatile("bar.sync 3, 288;" ::: "memory");
        if (warp < OUT_COLS) {
            const float a = bfr(warp_sum(red[warp * NHEAD + lane]));
            if (lane == 0) out[cta * OUT_COLS + warp] = __float2bfloat16_rn(bfr(xcol + a) + misc[40 + warp]);
        }
        TL(7);
    }
}

}

extern "C" void kernel_launch(void* const* d_in, const int* in_sizes, int n_in, void* d_out, int out_size) {
    const __nv_bfloat16* x = (const __nv_bfloat16*)d_in[0];
    const __nv_bfloat16* kc = (const __nv_bfloat16*)d_in[1];
    const __nv_bfloat16* vc = (const __nv_bfloat16*)d_in[2];
    const __nv_bfloat16* wq = (const __nv_bfloat16*)d_in[3];
    const __nv_bfloat16* wo = (const __nv_bfloat16*)d_in[4];
    const __nv_bfloat16* w1 = (const __nv_bfloat16*)d_in[6];
    const __nv_bfloat16* b1 = (const __nv_bfloat16*)d_in[7];
    const __nv_bfloat16* w2 = (const __nv_bfloat16*)d_in[8];
    const __nv_bfloat16* b2 = (const __nv_bfloat16*)d_in[9];
    static bool attr_set = false;
    if (!attr_set) {
        cudaFuncSetAttribute(fused_decode_kernel, cudaFuncAttributeMaxDynamicSharedMemorySize, SMEM_BYTES);
        attr_set = true;
    }
    fused_decode_kernel<<<NCTA, NTHREADS, SMEM_BYTES>>>(x, kc, vc, wq, wo, w1, b1, w2, b2, (__nv_bfloat16*)d_out);
}
```
